```python
import torch

def _softmax(x, axis=-1):
    return torch.softmax(x, dim=axis)

def _gelu(x):
    return torch.nn.functional.gelu(x, approximate='tanh')

def _silu(x):
    return torch.nn.functional.silu(x)

def _sigmoid(x):
    return torch.sigmoid(x)

def _layernorm(x, axis=-1, eps=1e-05):
    m = x.mean(dim=axis, keepdim=True)
    v = x.var(dim=axis, keepdim=True, unbiased=False)
    return (x - m) / torch.sqrt(v + eps)

def _scatter_add(tgt, idx, src, axis=0):
    return tgt.clone().index_add_(axis, idx, src)

def _segment_sum(src, seg, n):
    out = torch.zeros((n,) + src.shape[1:], dtype=src.dtype)
    return out.index_add_(0, seg, src)

def _pad(x, pw):
    flat = tuple((v for pair in reversed(pw) for v in pair))
    return torch.nn.functional.pad(x, flat)
kernel_name = 'sequential_preLN__linear_kernel_hedgehog__mixer_gmlp__prompt'

def setup_inputs():

    _w = lambda a: (lambda t: t.to(torch.bfloat16) if t.is_floating_point() else t)(torch.as_tensor(a))

    def _A_setup():
        B, S, D, H = (1, 2048, 512, 32)
        Dh = D // H
        return {'x': _w((lambda *s: torch.randn(*s, dtype=torch.bfloat16) * 0.05)(B, S, D)), 'wqkv': _w((lambda *s: torch.randn(*s, dtype=torch.bfloat16) * 0.2)(D, 3 * D)), 'w_phi': _w((lambda *s: torch.randn(*s, dtype=torch.bfloat16) * 0.2)(H, Dh, Dh) * Dh ** (-0.5)), 'wo': _w((lambda *s: torch.randn(*s, dtype=torch.bfloat16) * 0.05)(D, D))}
    _A_in = _A_setup()

    def _B_setup():
        B, S, D, F = (1, 2048, 512, 1376)
        Fh = F // 2
        return {'x': _w((lambda *s: torch.randn(*s, dtype=torch.bfloat16) * 0.05)(B, S, D)), 'w_in': _w((lambda *s: torch.randn(*s, dtype=torch.bfloat16) * 0.2)(D, 2 * Fh)), 'w_sp': _w(0.01 * (lambda *s: torch.randn(*s, dtype=torch.bfloat16) * 0.2)(S, S)), 'b_sp': _w(1.0 + 0.01 * (lambda *s: torch.randn(*s, dtype=torch.bfloat16) * 0.05)(S)), 'w_out': _w((lambda *s: torch.randn(*s, dtype=torch.bfloat16) * 0.05)(Fh, D))}
    _B_in = _B_setup()
    return {'A_x': _A_in['x'], 'A_wqkv': _A_in['wqkv'], 'A_w_phi': _A_in['w_phi'], 'A_wo': _A_in['wo'], 'B_x': _B_in['x'], 'B_w_in': _B_in['w_in'], 'B_w_sp': _B_in['w_sp'], 'B_b_sp': _B_in['b_sp'], 'B_w_out': _B_in['w_out']}

def reference(A_x, A_wqkv, A_w_phi, A_wo, B_x, B_w_in, B_w_sp, B_b_sp, B_w_out):

    def _A_ref(x, wqkv, w_phi, wo):
        B, S, D = x.shape
        H = 32
        Dh = D // H
        qkv = (lambda x, *d: x.permute(*d))((x @ wqkv).reshape(B, S, 3, H, Dh), 2, 0, 3, 1, 4)
        q, k, v = (qkv[0], qkv[1], qkv[2])
        pq = torch.einsum('bhsd,hdf->bhsf', q, w_phi)
        pk = torch.einsum('bhsd,hdf->bhsf', k, w_phi)
        phi_q = torch.concatenate([_softmax(pq, axis=-1), _softmax(-pq, axis=-1)], axis=-1)
        phi_k = torch.concatenate([_softmax(pk, axis=-1), _softmax(-pk, axis=-1)], axis=-1)
        kv = torch.einsum('bhsf,bhsd->bhfd', phi_k, v)
        z = torch.einsum('bhsf->bhf', phi_k)
        num = torch.einsum('bhqf,bhfd->bhqd', phi_q, kv)
        den = torch.einsum('bhqf,bhf->bhq', phi_q, z)[..., None] + 1e-06
        o = num / den
        return (lambda x, *d: x.permute(*d))(o, 0, 2, 1, 3).reshape(B, S, D) @ wo

    def _B_ref(x, w_in, w_sp, b_sp, w_out):
        B, S, D = x.shape
        F = w_in.shape[-1]
        Fh = F // 2
        z = _gelu(torch.einsum('bsd,df->bsf', x, w_in))
        z1 = z[..., :Fh].clone()
        z2 = _layernorm(z[..., Fh:], axis=-1)
        g = torch.einsum('ts,bsf->btf', w_sp, z2) + b_sp[None, :, None]
        return torch.einsum('bsf,fd->bsd', z1 * g, w_out)
    x = A_x
    h = x + _A_ref(_layernorm(x, axis=-1), A_wqkv, A_w_phi, A_wo)
    h2 = h + _B_ref(_layernorm(h, axis=-1), B_w_in, B_w_sp, B_b_sp, B_w_out)
    return h2
```

```cpp
#include <cuda_runtime.h>
#include <cuda.h>
#include <cuda_bf16.h>
#include <stdint.h>

typedef __nv_bfloat16 bf16;

__device__ __forceinline__ void wgmma_n128_t01(float (&d)[64], uint64_t da, uint64_t db, int sd) {
  asm volatile("{\n.reg .pred p;\nsetp.ne.b32 p, %66, 0;\n"
    "wgmma.mma_async.sync.aligned.m64n128k16.f32.bf16.bf16 {%0, %1, %2, %3, %4, %5, %6, %7, %8, %9, %10, %11, %12, %13, %14, %15, %16, %17, %18, %19, %20, %21, %22, %23, %24, %25, %26, %27, %28, %29, %30, %31, %32, %33, %34, %35, %36, %37, %38, %39, %40, %41, %42, %43, %44, %45, %46, %47, %48, %49, %50, %51, %52, %53, %54, %55, %56, %57, %58, %59, %60, %61, %62, %63}, %64, %65, p, 1, 1, 0, 1;\n}\n"
    : "+f"(d[0]), "+f"(d[1]), "+f"(d[2]), "+f"(d[3]), "+f"(d[4]), "+f"(d[5]), "+f"(d[6]), "+f"(d[7]), "+f"(d[8]), "+f"(d[9]), "+f"(d[10]), "+f"(d[11]), "+f"(d[12]), "+f"(d[13]), "+f"(d[14]), "+f"(d[15]), "+f"(d[16]), "+f"(d[17]), "+f"(d[18]), "+f"(d[19]), "+f"(d[20]), "+f"(d[21]), "+f"(d[22]), "+f"(d[23]), "+f"(d[24]), "+f"(d[25]), "+f"(d[26]), "+f"(d[27]), "+f"(d[28]), "+f"(d[29]), "+f"(d[30]), "+f"(d[31]), "+f"(d[32]), "+f"(d[33]), "+f"(d[34]), "+f"(d[35]), "+f"(d[36]), "+f"(d[37]), "+f"(d[38]), "+f"(d[39]), "+f"(d[40]), "+f"(d[41]), "+f"(d[42]), "+f"(d[43]), "+f"(d[44]), "+f"(d[45]), "+f"(d[46]), "+f"(d[47]), "+f"(d[48]), "+f"(d[49]), "+f"(d[50]), "+f"(d[51]), "+f"(d[52]), "+f"(d[53]), "+f"(d[54]), "+f"(d[55]), "+f"(d[56]), "+f"(d[57]), "+f"(d[58]), "+f"(d[59]), "+f"(d[60]), "+f"(d[61]), "+f"(d[62]), "+f"(d[63])
    : "l"(da), "l"(db), "r"(sd));
}
__device__ __forceinline__ void wgmma_n64_t01(float (&d)[32], uint64_t da, uint64_t db, int sd) {
  asm volatile("{\n.reg .pred p;\nsetp.ne.b32 p, %34, 0;\n"
    "wgmma.mma_async.sync.aligned.m64n64k16.f32.bf16.bf16 {%0, %1, %2, %3, %4, %5, %6, %7, %8, %9, %10, %11, %12, %13, %14, %15, %16, %17, %18, %19, %20, %21, %22, %23, %24, %25, %26, %27, %28, %29, %30, %31}, %32, %33, p, 1, 1, 0, 1;\n}\n"
    : "+f"(d[0]), "+f"(d[1]), "+f"(d[2]), "+f"(d[3]), "+f"(d[4]), "+f"(d[5]), "+f"(d[6]), "+f"(d[7]), "+f"(d[8]), "+f"(d[9]), "+f"(d[10]), "+f"(d[11]), "+f"(d[12]), "+f"(d[13]), "+f"(d[14]), "+f"(d[15]), "+f"(d[16]), "+f"(d[17]), "+f"(d[18]), "+f"(d[19]), "+f"(d[20]), "+f"(d[21]), "+f"(d[22]), "+f"(d[23]), "+f"(d[24]), "+f"(d[25]), "+f"(d[26]), "+f"(d[27]), "+f"(d[28]), "+f"(d[29]), "+f"(d[30]), "+f"(d[31])
    : "l"(da), "l"(db), "r"(sd));
}
__device__ __forceinline__ void wgmma_n88_t01(float (&d)[44], uint64_t da, uint64_t db, int sd) {
  asm volatile("{\n.reg .pred p;\nsetp.ne.b32 p, %46, 0;\n"
    "wgmma.mma_async.sync.aligned.m64n88k16.f32.bf16.bf16 {%0, %1, %2, %3, %4, %5, %6, %7, %8, %9, %10, %11, %12, %13, %14, %15, %16, %17, %18, %19, %20, %21, %22, %23, %24, %25, %26, %27, %28, %29, %30, %31, %32, %33, %34, %35, %36, %37, %38, %39, %40, %41, %42, %43}, %44, %45, p, 1, 1, 0, 1;\n}\n"
    : "+f"(d[0]), "+f"(d[1]), "+f"(d[2]), "+f"(d[3]), "+f"(d[4]), "+f"(d[5]), "+f"(d[6]), "+f"(d[7]), "+f"(d[8]), "+f"(d[9]), "+f"(d[10]), "+f"(d[11]), "+f"(d[12]), "+f"(d[13]), "+f"(d[14]), "+f"(d[15]), "+f"(d[16]), "+f"(d[17]), "+f"(d[18]), "+f"(d[19]), "+f"(d[20]), "+f"(d[21]), "+f"(d[22]), "+f"(d[23]), "+f"(d[24]), "+f"(d[25]), "+f"(d[26]), "+f"(d[27]), "+f"(d[28]), "+f"(d[29]), "+f"(d[30]), "+f"(d[31]), "+f"(d[32]), "+f"(d[33]), "+f"(d[34]), "+f"(d[35]), "+f"(d[36]), "+f"(d[37]), "+f"(d[38]), "+f"(d[39]), "+f"(d[40]), "+f"(d[41]), "+f"(d[42]), "+f"(d[43])
    : "l"(da), "l"(db), "r"(sd));
}
__device__ __forceinline__ void wgmma_n176_t01(float (&d)[88], uint64_t da, uint64_t db, int sd) {
  asm volatile("{\n.reg .pred p;\nsetp.ne.b32 p, %90, 0;\n"
    "wgmma.mma_async.sync.aligned.m64n176k16.f32.bf16.bf16 {%0, %1, %2, %3, %4, %5, %6, %7, %8, %9, %10, %11, %12, %13, %14, %15, %16, %17, %18, %19, %20, %21, %22, %23, %24, %25, %26, %27, %28, %29, %30, %31, %32, %33, %34, %35, %36, %37, %38, %39, %40, %41, %42, %43, %44, %45, %46, %47, %48, %49, %50, %51, %52, %53, %54, %55, %56, %57, %58, %59, %60, %61, %62, %63, %64, %65, %66, %67, %68, %69, %70, %71, %72, %73, %74, %75, %76, %77, %78, %79, %80, %81, %82, %83, %84, %85, %86, %87}, %88, %89, p, 1, 1, 0, 1;\n}\n"
    : "+f"(d[0]), "+f"(d[1]), "+f"(d[2]), "+f"(d[3]), "+f"(d[4]), "+f"(d[5]), "+f"(d[6]), "+f"(d[7]), "+f"(d[8]), "+f"(d[9]), "+f"(d[10]), "+f"(d[11]), "+f"(d[12]), "+f"(d[13]), "+f"(d[14]), "+f"(d[15]), "+f"(d[16]), "+f"(d[17]), "+f"(d[18]), "+f"(d[19]), "+f"(d[20]), "+f"(d[21]), "+f"(d[22]), "+f"(d[23]), "+f"(d[24]), "+f"(d[25]), "+f"(d[26]), "+f"(d[27]), "+f"(d[28]), "+f"(d[29]), "+f"(d[30]), "+f"(d[31]), "+f"(d[32]), "+f"(d[33]), "+f"(d[34]), "+f"(d[35]), "+f"(d[36]), "+f"(d[37]), "+f"(d[38]), "+f"(d[39]), "+f"(d[40]), "+f"(d[41]), "+f"(d[42]), "+f"(d[43]), "+f"(d[44]), "+f"(d[45]), "+f"(d[46]), "+f"(d[47]), "+f"(d[48]), "+f"(d[49]), "+f"(d[50]), "+f"(d[51]), "+f"(d[52]), "+f"(d[53]), "+f"(d[54]), "+f"(d[55]), "+f"(d[56]), "+f"(d[57]), "+f"(d[58]), "+f"(d[59]), "+f"(d[60]), "+f"(d[61]), "+f"(d[62]), "+f"(d[63]), "+f"(d[64]), "+f"(d[65]), "+f"(d[66]), "+f"(d[67]), "+f"(d[68]), "+f"(d[69]), "+f"(d[70]), "+f"(d[71]), "+f"(d[72]), "+f"(d[73]), "+f"(d[74]), "+f"(d[75]), "+f"(d[76]), "+f"(d[77]), "+f"(d[78]), "+f"(d[79]), "+f"(d[80]), "+f"(d[81]), "+f"(d[82]), "+f"(d[83]), "+f"(d[84]), "+f"(d[85]), "+f"(d[86]), "+f"(d[87])
    : "l"(da), "l"(db), "r"(sd));
}
__device__ __forceinline__ void wgmma_n40_t11(float (&d)[20], uint64_t da, uint64_t db, int sd) {
  asm volatile("{\n.reg .pred p;\nsetp.ne.b32 p, %22, 0;\n"
    "wgmma.mma_async.sync.aligned.m64n40k16.f32.bf16.bf16 {%0, %1, %2, %3, %4, %5, %6, %7, %8, %9, %10, %11, %12, %13, %14, %15, %16, %17, %18, %19}, %20, %21, p, 1, 1, 1, 1;\n}\n"
    : "+f"(d[0]), "+f"(d[1]), "+f"(d[2]), "+f"(d[3]), "+f"(d[4]), "+f"(d[5]), "+f"(d[6]), "+f"(d[7]), "+f"(d[8]), "+f"(d[9]), "+f"(d[10]), "+f"(d[11]), "+f"(d[12]), "+f"(d[13]), "+f"(d[14]), "+f"(d[15]), "+f"(d[16]), "+f"(d[17]), "+f"(d[18]), "+f"(d[19])
    : "l"(da), "l"(db), "r"(sd));
}

__device__ __align__(1024) uint32_t g_obuf[32 * 64 * 256];
__device__ __align__(1024) uint32_t g_hbuf[32 * 64 * 256];
__device__ __align__(1024) uint32_t g_ubuf[32 * 88 * 256];
__device__ __align__(1024) uint32_t g_zbuf[32 * 88 * 256];
#define KV_PITCH 40
#define KV_HEAD (17 * KV_PITCH)
__device__ __align__(128) float g_kv[2][32 * KV_HEAD];
__device__ __align__(128) float g_cs[2][8 * 384];
__device__ __align__(128) float2 g_st1[2048];
__device__ __align__(128) float2 g_st2[2048 * 8];
__device__ __align__(128) unsigned long long g_st3[2048 * 16];
__device__ __align__(128) unsigned g_f0[8 * 32];
__device__ __align__(128) unsigned g_fs[16 * 32];
__device__ __align__(128) unsigned g_fc[8 * 32];
__device__ __align__(128) unsigned g_fo[32 * 32];
__device__ __align__(128) unsigned g_fh[32 * 32];
__device__ __align__(128) unsigned g_fz[32 * 32];
__device__ __align__(128) unsigned g_fu[32 * 32];
#define STAMP(i)

struct alignas(64) Params {
    CUtensorMap mx, mwqkv, mwo, mwin, mwsp, mwout;
    const bf16 *x, *wqkv, *wphi, *wo, *win, *wsp, *bsp, *wout;
    bf16* out;
    int use_smid;
};

constexpr uint32_t OFF_X = 0;
constexpr uint32_t OFF_W = 131072;
constexpr uint32_t OFF_MISC = 131072 + 86016;
constexpr uint32_t OFF_ST1 = OFF_MISC;
constexpr uint32_t OFF_ST2 = OFF_MISC + 1024;
constexpr uint32_t OFF_CS = OFF_MISC + 2048;
constexpr uint32_t OFF_BSP = OFF_MISC + 3584;
constexpr uint32_t OFF_EP = OFF_MISC + 4096;
constexpr uint32_t OFF_BAR = OFF_MISC + 4224;
constexpr uint32_t SMEM_USED = OFF_BAR + 1024;
constexpr uint32_t SMEM_BYTES = SMEM_USED + 1024;
constexpr uint32_t OFF_SLOT = OFF_W + 4096;
constexpr uint32_t OFF_PHI = OFF_W;
constexpr uint32_t OFF_VST = OFF_W + 32768;
constexpr uint32_t OFF_KVS = OFF_W;
constexpr uint32_t OFF_O = OFF_W + 20480;
constexpr uint32_t P3_STAGE = 16384 + 22528;
constexpr uint32_t OFF_XC = 4 * P3_STAGE;
constexpr uint32_t OFF_U = 7 * 16384;

enum {
    B_X = 0, B_W = 8, B_Q = 16, B_KV = 20, B_WO = 21, B_O = 22, B_H = 30, B_WI = 46, B_XC = 62, B_WT = 63, B_U = 74,
    B_C2 = 82,
    B_EW = 82, B_EQ = 87, B_DQ = 89, B_DA = 90, B_EI = 91, B_AUX2 = 100, B_DZ = 101, B_F = 102, B_E = 106, B_D3 = 110, B_DU = 111,
    B_ET = 112, B_PR = 116,
    B_AUX1 = 117,
    NBAR = 118
};

#define SPIN_LIMIT (1 << 22)
__device__ __forceinline__ uint32_t smem_u32(const void* p) { return (uint32_t)__cvta_generic_to_shared(p); }
__device__ __forceinline__ void mbar_init(uint32_t bar, int cnt) { asm volatile("mbarrier.init.shared::cta.b64 [%0], %1;" :: "r"(bar), "r"(cnt) : "memory"); }
__device__ __forceinline__ void mbar_expect(uint32_t bar, uint32_t bytes) { asm volatile("mbarrier.arrive.expect_tx.shared::cta.b64 _, [%0], %1;" :: "r"(bar), "r"(bytes) : "memory"); }
__device__ __forceinline__ void mbar_arrive(uint32_t bar) { asm volatile("mbarrier.arrive.shared::cta.b64 _, [%0];" :: "r"(bar) : "memory"); }
__device__ __forceinline__ void mbar_wait(uint32_t bar, uint32_t parity) {
    uint32_t ok; int guard = 0;
    while (true) {
        asm volatile("{\n.reg .pred p;\nmbarrier.try_wait.parity.shared::cta.b64 p, [%1], %2;\nselp.u32 %0, 1, 0, p;\n}" : "=r"(ok) : "r"(bar), "r"(parity) : "memory");
        if (ok) break;
        if (++guard > SPIN_LIMIT) __trap();
    }
}
__device__ __forceinline__ void mbar_wait_cluster(uint32_t bar, uint32_t parity) {
    uint32_t ok; int guard = 0;
    while (true) {
        asm volatile("{\n.reg .pred p;\nmbarrier.try_wait.parity.acquire.cluster.shared::cta.b64 p, [%1], %2;\nselp.u32 %0, 1, 0, p;\n}" : "=r"(ok) : "r"(bar), "r"(parity) : "memory");
        if (ok) break;
        if (++guard > SPIN_LIMIT) __trap();
    }
}
__device__ __forceinline__ void tma2d(uint32_t dst, const CUtensorMap* m, int c0, int c1, uint32_t bar) {
    asm volatile("cp.async.bulk.tensor.2d.shared::cluster.global.mbarrier::complete_tx::bytes [%0], [%1, {%3, %4}], [%2];"
                 :: "r"(dst), "l"(m), "r"(bar), "r"(c0), "r"(c1) : "memory");
}
__device__ __forceinline__ void bulk1d(uint32_t dst, const void* src, uint32_t bytes, uint32_t bar) {
    asm volatile("cp.async.bulk.shared::cluster.global.mbarrier::complete_tx::bytes [%0], [%1], %2, [%3];"
                 :: "r"(dst), "l"(src), "r"(bytes), "r"(bar) : "memory");
}
__device__ __forceinline__ void l2_prefetch(const void* src, uint32_t bytes) {
    asm volatile("cp.async.bulk.prefetch.L2.global [%0], %1;" :: "l"(src), "r"(bytes) : "memory");
}
__device__ __forceinline__ unsigned ld_acquire(const unsigned* p) { unsigned v; asm volatile("ld.acquire.gpu.global.u32 %0, [%1];" : "=r"(v) : "l"(p) : "memory"); return v; }
__device__ __forceinline__ unsigned ld_relaxed(const unsigned* p) { unsigned v; asm volatile("ld.relaxed.gpu.global.u32 %0, [%1];" : "=r"(v) : "l"(p) : "memory"); return v; }
__device__ __forceinline__ void st_release(unsigned* p, unsigned v) { asm volatile("st.release.gpu.global.u32 [%0], %1;" :: "l"(p), "r"(v) : "memory"); }
__device__ __forceinline__ void red_release(unsigned* p, unsigned v) { asm volatile("red.release.gpu.global.add.u32 [%0], %1;" :: "l"(p), "r"(v) : "memory"); }
__device__ __forceinline__ void red_relaxed(unsigned* p, unsigned v) { asm volatile("red.relaxed.gpu.global.add.u32 [%0], %1;" :: "l"(p), "r"(v) : "memory"); }
__device__ __forceinline__ void red_f32(float* p, float v) { asm volatile("red.relaxed.gpu.global.add.f32 [%0], %1;" :: "l"(p), "f"(v) : "memory"); }
__device__ __forceinline__ void wait_flag(const unsigned* p, unsigned target) {
    int guard = 0;
    while ((int)(ld_acquire(p) - target) < 0) { if (++guard > SPIN_LIMIT) __trap(); }
}
__device__ __forceinline__ void fence_async_global() { asm volatile("fence.proxy.async.global;" ::: "memory"); }
__device__ __forceinline__ void fence_async_smem() { asm volatile("fence.proxy.async.shared::cta;" ::: "memory"); }
__device__ __forceinline__ void bar_sync(int id, int n) { asm volatile("bar.sync %0, %1;" :: "r"(id), "r"(n) : "memory"); }
__device__ __forceinline__ void wg_fence() { asm volatile("wgmma.fence.sync.aligned;" ::: "memory"); }
__device__ __forceinline__ void wg_commit() { asm volatile("wgmma.commit_group.sync.aligned;" ::: "memory"); }
template <int N> __device__ __forceinline__ void wg_wait() { asm volatile("wgmma.wait_group.sync.aligned %0;" :: "n"(N) : "memory"); }
template <int N> __device__ __forceinline__ void pin(float (&d)[N]) {
#pragma unroll
    for (int i = 0; i < N; i++) asm volatile("" : "+f"(d[i]) :: "memory");
}
__device__ __forceinline__ uint64_t mkdesc(uint32_t addr, uint32_t lbo, uint32_t sbo, uint32_t layout) {
    return (uint64_t)((addr & 0x3FFFF) >> 4) | ((uint64_t)(lbo >> 4) << 16) | ((uint64_t)(sbo >> 4) << 32) | ((uint64_t)layout << 62);
}
__device__ __forceinline__ uint32_t pack2(float lo, float hi) { uint32_t r; asm("cvt.rn.bf16x2.f32 %0, %1, %2;" : "=r"(r) : "f"(hi), "f"(lo)); return r; }
__device__ __forceinline__ float lo_f(uint32_t w) { return __uint_as_float(w << 16); }
__device__ __forceinline__ float hi_f(uint32_t w) { return __uint_as_float(w & 0xffff0000u); }
__device__ __forceinline__ float ex2(float x) { float r; asm("ex2.approx.ftz.f32 %0, %1;" : "=f"(r) : "f"(x)); return r; }
__device__ __forceinline__ float rcp(float x) { float r; asm("rcp.approx.ftz.f32 %0, %1;" : "=f"(r) : "f"(x)); return r; }
__device__ __forceinline__ float gelu_tanh(float v) {
    float u = v * (0.7978845608028654f + 0.035677408136300125f * v * v);
    float t; asm("tanh.approx.f32 %0, %1;" : "=f"(t) : "f"(u));
    float hv = 0.5f * v;
    return fmaf(hv, t, hv);
}
__device__ __forceinline__ void mma16816(float (&c)[4], uint32_t a0, uint32_t a1, uint32_t a2, uint32_t a3, uint32_t b0, uint32_t b1) {
    asm volatile("mma.sync.aligned.m16n8k16.row.col.f32.bf16.bf16.f32 {%0,%1,%2,%3}, {%4,%5,%6,%7}, {%8,%9}, {%0,%1,%2,%3};"
                 : "+f"(c[0]), "+f"(c[1]), "+f"(c[2]), "+f"(c[3]) : "r"(a0), "r"(a1), "r"(a2), "r"(a3), "r"(b0), "r"(b1));
}
__device__ __forceinline__ void stsm4(uint32_t addr, uint32_t r0, uint32_t r1, uint32_t r2, uint32_t r3) {
    asm volatile("stmatrix.sync.aligned.m8n8.x4.shared.b16 [%0], {%1,%2,%3,%4};" :: "r"(addr), "r"(r0), "r"(r1), "r"(r2), "r"(r3) : "memory");
}
__device__ __forceinline__ float2 lds_f2(uint32_t a) { float2 v; asm volatile("ld.shared.v2.f32 {%0,%1}, [%2];" : "=f"(v.x), "=f"(v.y) : "r"(a) : "memory"); return v; }
__device__ __forceinline__ float lds_f(uint32_t a) { float v; asm volatile("ld.shared.f32 %0, [%1];" : "=f"(v) : "r"(a) : "memory"); return v; }
__device__ __forceinline__ uint32_t lds_u(uint32_t a) { uint32_t v; asm volatile("ld.shared.u32 %0, [%1];" : "=r"(v) : "r"(a) : "memory"); return v; }
__device__ __forceinline__ void sts_f2(uint32_t a, float x, float y) { asm volatile("st.shared.v2.f32 [%0], {%1,%2};" :: "r"(a), "f"(x), "f"(y) : "memory"); }
__device__ __forceinline__ void sts_f(uint32_t a, float x) { asm volatile("st.shared.f32 [%0], %1;" :: "r"(a), "f"(x) : "memory"); }
__device__ __forceinline__ float quad_sum(float v) { v += __shfl_xor_sync(0xffffffffu, v, 1); v += __shfl_xor_sync(0xffffffffu, v, 2); return v; }
__device__ __forceinline__ float quad_max(float v) { v = fmaxf(v, __shfl_xor_sync(0xffffffffu, v, 1)); v = fmaxf(v, __shfl_xor_sync(0xffffffffu, v, 2)); return v; }
__device__ __forceinline__ float quad_min(float v) { v = fminf(v, __shfl_xor_sync(0xffffffffu, v, 1)); v = fminf(v, __shfl_xor_sync(0xffffffffu, v, 2)); return v; }

#define POLL_ISSUE(NL, FLAGPTR, ISSUE) { \
        bool done_ = lane >= (NL); const unsigned* fp_ = (FLAGPTR); int guard_ = 0; \
        while (true) { \
            if (!done_ && (int)(ld_acquire(fp_) - epoch) >= 0) { fence_async_global(); ISSUE; done_ = true; } \
            if (__all_sync(0xffffffffu, done_)) break; \
            if (++guard_ > SPIN_LIMIT) __trap(); \
        } }

__device__ __forceinline__ void feature_map(uint32_t a0, uint32_t a1, uint32_t a2, uint32_t a3, const uint32_t* wb, uint32_t* pos, uint32_t* neg) {
    const float L2E = 1.4426950408889634f;
    float c0[4] = {0.f, 0.f, 0.f, 0.f}, c1[4] = {0.f, 0.f, 0.f, 0.f};
    mma16816(c0, a0, a1, a2, a3, wb[0], wb[1]);
    mma16816(c1, a0, a1, a2, a3, wb[2], wb[3]);
#pragma unroll
    for (int rr = 0; rr < 2; rr++) {
        float p0 = c0[2 * rr] * L2E, p1 = c0[2 * rr + 1] * L2E, p2 = c1[2 * rr] * L2E, p3 = c1[2 * rr + 1] * L2E;
        float mx = quad_max(fmaxf(fmaxf(p0, p1), fmaxf(p2, p3)));
        float mn = quad_min(fminf(fminf(p0, p1), fminf(p2, p3)));
        float e0 = ex2(p0 - mx), e1 = ex2(p1 - mx), e2 = ex2(p2 - mx), e3 = ex2(p3 - mx);
        float f0 = ex2(mn - p0), f1 = ex2(mn - p1), f2 = ex2(mn - p2), f3 = ex2(mn - p3);
        float se = rcp(quad_sum((e0 + e1) + (e2 + e3)));
        float sf = rcp(quad_sum((f0 + f1) + (f2 + f3)));
        pos[rr] = pack2(e0 * se, e1 * se); pos[2 + rr] = pack2(e2 * se, e3 * se);
        neg[rr] = pack2(f0 * sf, f1 * sf); neg[2 + rr] = pack2(f2 * sf, f3 * sf);
    }
}

__device__ __forceinline__ int pair_from_tpc(int t) {
    int g, slot;
    if (t < 32) { g = t & 7; slot = t >> 3; }
    else if (t < 60) { g = 1 + (t - 32) % 7; slot = 4 + (t - 32) / 7; }
    else if (t < 62) return -1;
    else { g = 0; slot = 4 + (t - 62); }
    return g * 8 + slot;
}

__global__ void __launch_bounds__(384, 1) fused_kernel(const __grid_constant__ Params P) {
    extern __shared__ __align__(1024) uint8_t smem_raw[];
    const uint32_t sb = (smem_u32(smem_raw) + 1023) & ~1023u;
    const int tid = threadIdx.x, warp = tid >> 5, lane = tid & 31;
    uint32_t rank; asm volatile("mov.u32 %0, %%cluster_ctarank;" : "=r"(rank));
    int pair;
    if (P.use_smid) { uint32_t smid; asm volatile("mov.u32 %0, %%smid;" : "=r"(smid)); pair = pair_from_tpc(smid >> 1); }
    else pair = blockIdx.x >> 1;
    if (pair < 0) {
        long long t0 = clock64();
        while (clock64() - t0 < 8000) {}
        return;
    }
    const int role = pair * 2 + rank;
    const int gg = role >> 4, ii = role & 15;
    const int r = (gg >> 1) * 4 + (ii >> 2);
    const int j = (gg & 1) * 4 + (ii & 3);
    const int rh = 2 * r + (j & 1), c4 = j >> 1;
    const uint32_t bar0 = sb + OFF_BAR;
#define BAR(i) (bar0 + 8 * (i))

    if (tid < NBAR) mbar_init(BAR(tid), tid < B_C2 ? 1 : (tid < B_AUX1 ? 2 : 3));
    asm volatile("fence.mbarrier_init.release.cluster;" ::: "memory");
    __syncthreads();
    asm volatile("barrier.cluster.arrive.release.aligned;" ::: "memory");

    if (warp == 8) {
        if (lane == 0) {
            for (int kb = 0; kb < 8; kb++) {
                mbar_expect(BAR(B_X + kb), 16384);
                tma2d(sb + OFF_X + kb * 16384, &P.mx, kb * 64, r * 128, BAR(B_X + kb));
                if (kb < 5) {
                    mbar_expect(BAR(B_W + kb), 16384);
                    tma2d(sb + OFF_SLOT + kb * 16384, &P.mwqkv, 512 + 64 * j, kb * 64, BAR(B_W + kb));
                    tma2d(sb + OFF_SLOT + kb * 16384 + 8192, &P.mwqkv, 1024 + 64 * j, kb * 64, BAR(B_W + kb));
                }
            }
        }
        const unsigned epoch = ld_relaxed(&g_f0[j * 32]) / 32u + 1u;
        if (lane == 0) {
            for (int kb = 5; kb < 8; kb++) {
                mbar_wait(BAR(B_EW + kb - 5), 0);
                mbar_expect(BAR(B_W + kb), 16384);
                tma2d(sb + OFF_SLOT + (kb - 5) * 16384, &P.mwqkv, 512 + 64 * j, kb * 64, BAR(B_W + kb));
                tma2d(sb + OFF_SLOT + (kb - 5) * 16384 + 8192, &P.mwqkv, 1024 + 64 * j, kb * 64, BAR(B_W + kb));
            }
            for (int q = 0; q < 4; q++) {
                mbar_wait(q < 2 ? BAR(B_EW + 3 + q) : BAR(B_EQ + q - 2), 0);
                uint32_t dst = sb + OFF_SLOT + (3 + (q & 1)) * 16384;
                mbar_expect(BAR(B_Q + q), 16384);
                tma2d(dst, &P.mwqkv, 64 * j, q * 128, BAR(B_Q + q));
                tma2d(dst + 8192, &P.mwqkv, 64 * j, q * 128 + 64, BAR(B_Q + q));
            }
            mbar_wait(BAR(B_DQ), 0);
            mbar_expect(BAR(B_WO), 131072);
            for (int q = 0; q < 4; q++)
                tma2d(sb + OFF_X + q * 32768, &P.mwo, 128 * c4 + 64 * (q >> 1), (q & 1) * 256, BAR(B_WO));
        }
        __syncwarp();
        POLL_ISSUE(8, &g_fo[rh * 32 + lane],
                   mbar_expect(BAR(B_O + lane), 8192);
                   bulk1d(sb + OFF_O + lane * 8192, g_obuf + (rh * 64 + lane * 8) * 256, 8192, BAR(B_O + lane)))
        mbar_wait(BAR(B_DA), 0);
        if (lane < 21) {
            int s = lane / 3, ch = lane % 3;
            if (ch == 0) mbar_expect(BAR(B_WI + s), 12288);
            tma2d(sb + OFF_W + s * 12288 + ch * 4096, &P.mwin, 688 + 88 * j + 32 * ch, s * 64, BAR(B_WI + s));
        }
        __syncwarp();
        POLL_ISSUE(16, &g_fh[(2 * r + ((lane >> 3) & 1)) * 32 + (lane & 7)],
                   mbar_expect(BAR(B_H + lane), 8192);
                   bulk1d(sb + OFF_X + lane * 8192, g_hbuf + (2 * r * 64 + lane * 8) * 256, 8192, BAR(B_H + lane)))
        for (int b = 7; b < 16; b++) {
            mbar_wait(BAR(B_EI + b - 7), 0);
            if (lane < 3) {
                if (lane == 0) mbar_expect(BAR(B_WI + b), 12288);
                tma2d(sb + OFF_W + (b % 7) * 12288 + lane * 4096, &P.mwin, (b < 8 ? 688 : 0) + 88 * j + 32 * lane, (b & 7) * 64, BAR(B_WI + b));
            }
            __syncwarp();
        }
        {
            const int nt = j >> 1, kh = j & 1;
            mbar_wait(BAR(B_DZ), 0);
            if (lane < 4) {
                mbar_expect(BAR(B_F + lane), 16384);
                tma2d(sb + lane * P3_STAGE, &P.mwsp, (kh * 16 + lane) * 64, r * 128, BAR(B_F + lane));
            }
            __syncwarp();
            const unsigned* fl = &g_fz[(kh * 16 + (lane >> 1)) * 32 + 2 * nt + (lane & 1)];
            unsigned ready = 0; bool mine = false;
            for (int it = 0; it < 16; it++) {
                int s = it & 3;
                int guard = 0;
                while (((ready >> (2 * it)) & 3u) != 3u) {
                    if (!mine) mine = (int)(ld_acquire(fl) - epoch) >= 0;
                    ready = __ballot_sync(0xffffffffu, mine);
                    if (++guard > SPIN_LIMIT) __trap();
                }
                __syncwarp();
                if (lane == 0) {
                    if (it >= 4) {
                        mbar_wait(BAR(B_E + s), ((it >> 2) - 1) & 1);
                        mbar_expect(BAR(B_F + s), 16384);
                        tma2d(sb + s * P3_STAGE, &P.mwsp, (kh * 16 + it) * 64, r * 128, BAR(B_F + s));
                    }
                    fence_async_global();
                    mbar_expect(BAR(B_F + s), 22528);
                    bulk1d(sb + s * P3_STAGE + 16384, g_zbuf + ((kh * 16 + it) * 88 + nt * 22) * 256, 22528, BAR(B_F + s));
                }
                __syncwarp();
            }
        }
        mbar_wait(BAR(B_D3), 0);
        if (lane < 14) {
            int s = lane >> 1, hf = lane & 1;
            if (hf == 0) mbar_expect(BAR(B_WT + s), 16384);
            tma2d(sb + s * 16384 + hf * 8192, &P.mwout, 128 * c4 + 64 * hf, s * 64, BAR(B_WT + s));
        }
        __syncwarp();
        mbar_wait(BAR(B_DU), 0);
        POLL_ISSUE(8, &g_fu[rh * 32 + lane],
                   mbar_expect(BAR(B_U + lane), lane == 7 ? 9216 : 11264);
                   bulk1d(sb + OFF_U + lane * 11264, g_ubuf + (rh * 88 + lane * 11) * 256, lane == 7 ? 9216 : 11264, BAR(B_U + lane)))
        for (int b = 7; b < 11; b++) {
            mbar_wait(BAR(B_ET + b - 7), 0);
            if (lane < 2) {
                if (lane == 0) mbar_expect(BAR(B_WT + b), 16384);
                tma2d(sb + (b - 7) * 16384 + lane * 8192, &P.mwout, 128 * c4 + 64 * lane, b * 64, BAR(B_WT + b));
            }
            __syncwarp();
        }
        asm volatile("barrier.cluster.wait.acquire.aligned;" ::: "memory");
    } else if (warp > 8) {
        const int atid = tid - 288;
        uint4 cw[16];
        const int chunk = atid >> 1;
        bool cvalid = atid < 92;
        {
            const bf16* ptr; int pitch;
            if (chunk < 24) { int which = chunk >> 3; ptr = P.wqkv + (which == 0 ? 512 : which == 1 ? 1024 : 0) + 64 * j + (chunk & 7) * 8; pitch = 1536; }
            else { int c2 = chunk - 24, part = c2 >= 11, cc = c2 - 11 * part; cvalid = cvalid && (88 * j + cc * 8 < 688);
                   ptr = P.win + (part ? 0 : 688) + 88 * j + cc * 8; pitch = 1376; }
            ptr += (size_t)(32 * r + 16 * (atid & 1)) * pitch;
#pragma unroll
            for (int q = 0; q < 16; q++) cw[q] = cvalid ? __ldg((const uint4*)(ptr + (size_t)q * pitch)) : make_uint4(0, 0, 0, 0);
        }
        uint4 xr[16];
        if (warp < 11) {
            const bf16* xp = P.x + (size_t)(128 * r + 16 * j + 8 * (warp - 9)) * 512 + lane * 8;
#pragma unroll
            for (int q = 0; q < 8; q++) { xr[2 * q] = __ldg((const uint4*)(xp + q * 512)); xr[2 * q + 1] = __ldg((const uint4*)(xp + q * 512 + 256)); }
        }
        const unsigned epoch = ld_relaxed(&g_f0[j * 32]) / 32u + 1u;
        const int par = epoch & 1;
        {
            float s[8] = {0, 0, 0, 0, 0, 0, 0, 0};
#pragma unroll
            for (int q = 0; q < 16; q++) {
                s[0] += lo_f(cw[q].x); s[1] += hi_f(cw[q].x); s[2] += lo_f(cw[q].y); s[3] += hi_f(cw[q].y);
                s[4] += lo_f(cw[q].z); s[5] += hi_f(cw[q].z); s[6] += lo_f(cw[q].w); s[7] += hi_f(cw[q].w);
            }
#pragma unroll
            for (int q = 0; q < 8; q++) s[q] += __shfl_xor_sync(0xffffffffu, s[q], 1);
            if (cvalid) {
                float* dst = &g_cs[par][j * 384 + chunk * 8 + (atid & 1) * 4];
#pragma unroll
                for (int q = 0; q < 4; q++) red_f32(dst + q, (atid & 1) ? s[4 + q] : s[q]);
            }
        }
        if (warp < 11) {
#pragma unroll
            for (int q = 0; q < 8; q++) {
                float v[16];
                const uint4 a = xr[2 * q], b = xr[2 * q + 1];
                v[0] = lo_f(a.x); v[1] = hi_f(a.x); v[2] = lo_f(a.y); v[3] = hi_f(a.y); v[4] = lo_f(a.z); v[5] = hi_f(a.z); v[6] = lo_f(a.w); v[7] = hi_f(a.w);
                v[8] = lo_f(b.x); v[9] = hi_f(b.x); v[10] = lo_f(b.y); v[11] = hi_f(b.y); v[12] = lo_f(b.z); v[13] = hi_f(b.z); v[14] = lo_f(b.w); v[15] = hi_f(b.w);
                float s = 0;
#pragma unroll
                for (int e = 0; e < 16; e++) s += v[e];
#pragma unroll
                for (int o = 16; o > 0; o >>= 1) s += __shfl_xor_sync(0xffffffffu, s, o);
                float mu = s * (1.f / 512.f), m2 = 0;
#pragma unroll
                for (int e = 0; e < 16; e++) { float d = v[e] - mu; m2 = fmaf(d, d, m2); }
#pragma unroll
                for (int o = 16; o > 0; o >>= 1) m2 += __shfl_xor_sync(0xffffffffu, m2, o);
                if (lane == 0) g_st1[128 * r + 16 * j + 8 * (warp - 9) + q] = make_float2(mu, rsqrtf(m2 * (1.f / 512.f) + 1e-5f));
            }
        }
        __syncwarp();
        if (lane == 0) {
            asm volatile("fence.acq_rel.gpu;" ::: "memory");
            red_relaxed(&g_fc[j * 32], 1);
            if (warp < 11) red_relaxed(&g_fs[r * 32], 1);
        }
        if (warp == 11) {
            if (lane == 0) {
                l2_prefetch((const char*)P.wo + role * 4096, 4096);
                l2_prefetch((const char*)P.win + role * 11008, 11008);
                l2_prefetch((const char*)P.wout + role * 5504, 5504);
                for (int q = 0; q < 4; q++) l2_prefetch((const char*)P.wsp + role * 65536 + q * 16384, 16384);
            }
            if (r == 0) {
                float4* z = (float4*)&g_kv[par ^ 1][j * 4 * KV_HEAD];
                for (int q = lane; q < KV_HEAD; q += 32) z[q] = make_float4(0, 0, 0, 0);
                float4* z2 = (float4*)&g_cs[par ^ 1][j * 384];
                for (int q = lane; q < 96; q += 32) z2[q] = make_float4(0, 0, 0, 0);
            }
#pragma unroll
            for (int q = 0; q < 4; q++) sts_f(sb + OFF_BSP + (q * 32 + lane) * 4, __bfloat162float(P.bsp[128 * r + q * 32 + lane]));
            if (lane == 0) asm volatile("st.shared.u32 [%0], %1;" :: "r"(sb + OFF_EP), "r"(epoch) : "memory");
        } else if (warp == 9) {
            if (lane == 0) wait_flag(&g_fs[r * 32], 16u * epoch);
            __syncwarp();
#pragma unroll
            for (int q = 0; q < 4; q++) { float2 v = __ldcg(&g_st1[128 * r + q * 32 + lane]); sts_f2(sb + OFF_ST1 + (q * 32 + lane) * 8, v.x, v.y); }
        } else {
            if (lane == 0) wait_flag(&g_fc[j * 32], 48u * epoch);
            __syncwarp();
#pragma unroll
            for (int q = 0; q < 12; q++) sts_f(sb + OFF_CS + (q * 32 + lane) * 4, __ldcg(&g_cs[par][j * 384 + q * 32 + lane]));
        }
        __syncwarp();
        if (lane == 0) mbar_arrive(BAR(B_AUX1));
        if (warp == 9) {
            if (lane == 0) {
                wait_flag(&g_f0[j * 32], 32u * epoch);
                fence_async_global();
                mbar_expect(BAR(B_KV), 4 * KV_HEAD * 4);
                bulk1d(sb + OFF_KVS, &g_kv[par][j * 4 * KV_HEAD], 4 * KV_HEAD * 4, BAR(B_KV));
            }
            __syncwarp();
        } else {
            const int half = warp - 10;
            if (lane < 8) wait_flag(&g_fh[(2 * r + half) * 32 + lane], epoch);
            __syncwarp();
#pragma unroll
            for (int q = 0; q < 2; q++) {
                int row = half * 64 + q * 32 + lane;
                const float4* p = (const float4*)&g_st2[(128 * r + row) * 8];
                float4 a = __ldcg(p), b = __ldcg(p + 1), c = __ldcg(p + 2), d = __ldcg(p + 3);
                float mu = ((a.x + a.z) + (b.x + b.z) + (c.x + c.z) + (d.x + d.z)) * (1.f / 8.f);
                float m2 = (a.y + a.w) + (b.y + b.w) + (c.y + c.w) + (d.y + d.w);
                float t, dd = 0;
                t = a.x - mu; dd = fmaf(t, t, dd); t = a.z - mu; dd = fmaf(t, t, dd); t = b.x - mu; dd = fmaf(t, t, dd); t = b.z - mu; dd = fmaf(t, t, dd);
                t = c.x - mu; dd = fmaf(t, t, dd); t = c.z - mu; dd = fmaf(t, t, dd); t = d.x - mu; dd = fmaf(t, t, dd); t = d.z - mu; dd = fmaf(t, t, dd);
                m2 = fmaf(dd, 64.f, m2);
                sts_f2(sb + OFF_ST2 + row * 8, mu, rsqrtf(m2 * (1.f / 512.f) + 1e-5f));
            }
            __syncwarp();
            if (lane == 0) mbar_arrive(BAR(B_AUX2));
        }
        asm volatile("barrier.cluster.wait.acquire.aligned;" ::: "memory");
    } else {
        const int wg = warp >> 2, w4 = warp & 3, g = lane >> 2, c = lane & 3;
        const bool elect = (tid & 127) == 0;
        uint32_t wb[16];
        {
            const unsigned short* wp = (const unsigned short*)P.wphi + (size_t)(4 * j) * 256;
#pragma unroll
            for (int hh = 0; hh < 4; hh++)
#pragma unroll
                for (int t = 0; t < 2; t++)
#pragma unroll
                    for (int kk = 0; kk < 2; kk++) {
                        const unsigned short* q = wp + hh * 256 + (2 * c + 8 * kk) * 16 + 8 * t + g;
                        wb[hh * 4 + t * 2 + kk] = (uint32_t)__ldg(q) | ((uint32_t)__ldg(q + 16) << 16);
                    }
        }
        uint32_t phq[32];
        unsigned epoch;
        {
            float akv[64], aq[32];
            const uint64_t dxa = mkdesc(sb + OFF_X + wg * 8192, 16, 1024, 1);
#pragma unroll
            for (int kb = 0; kb < 8; kb++) {
                mbar_wait(BAR(B_X + kb), 0);
                mbar_wait(BAR(B_W + kb), 0);
                if (kb == 0) STAMP(0);
                const uint64_t db = mkdesc(sb + OFF_SLOT + (kb % 5) * 16384, 8192, 1024, 1);
                wg_fence();
#pragma unroll
                for (int ks = 0; ks < 4; ks++) wgmma_n128_t01(akv, dxa + kb * 1024 + ks * 2, db + ks * 128, (kb | ks) != 0);
                wg_commit();
                if (kb >= 1 && kb <= 5) { wg_wait<1>(); if (elect) mbar_arrive(BAR(B_EW + kb - 1)); }
            }
#pragma unroll
            for (int q = 0; q < 2; q++) {
                mbar_wait(BAR(B_Q + q), 0);
                const uint64_t db = mkdesc(sb + OFF_SLOT + (3 + q) * 16384, 8192, 1024, 1);
                wg_fence();
#pragma unroll
                for (int ks = 0; ks < 8; ks++) wgmma_n64_t01(aq, dxa + (2 * q + (ks >> 2)) * 1024 + (ks & 3) * 2, db + ks * 128, (q | ks) != 0);
                wg_commit();
            }
            wg_wait<2>();
            pin(akv);
            STAMP(1);
            mbar_wait(BAR(B_AUX1), 0);
            epoch = lds_u(sb + OFF_EP);
            const float2 s0 = lds_f2(sb + OFF_ST1 + (wg * 64 + w4 * 16 + g) * 8), s1 = lds_f2(sb + OFF_ST1 + (wg * 64 + w4 * 16 + g + 8) * 8);
            bar_sync(1, 256);
            const int tg = 8 * wg + 2 * w4;
            const uint32_t stoff = ((lane >> 4) & 1) * 2048 + (tg + ((lane >> 3) & 1)) * 128 + (lane & 7) * 16;
#pragma unroll
            for (int hh = 0; hh < 4; hh++) {
                uint32_t a[4];
#pragma unroll
                for (int t = 0; t < 2; t++) {
                    const float2 cs = lds_f2(sb + OFF_CS + (hh * 16 + t * 8 + 2 * c) * 4);
                    const int i = (2 * hh + t) * 4;
                    a[2 * t] = pack2((akv[i] - s0.x * cs.x) * s0.y, (akv[i + 1] - s0.x * cs.y) * s0.y);
                    a[2 * t + 1] = pack2((akv[i + 2] - s1.x * cs.x) * s1.y, (akv[i + 3] - s1.x * cs.y) * s1.y);
                }
                uint32_t pos[4], neg[4];
                feature_map(a[0], a[1], a[2], a[3], &wb[hh * 4], pos, neg);
                stsm4(sb + OFF_PHI + (4 * hh) * 2048 + stoff, pos[0], pos[1], pos[2], pos[3]);
                stsm4(sb + OFF_PHI + (4 * hh + 2) * 2048 + stoff, neg[0], neg[1], neg[2], neg[3]);
#pragma unroll
                for (int t = 0; t < 2; t++) {
                    const float2 cs = lds_f2(sb + OFF_CS + (64 + hh * 16 + t * 8 + 2 * c) * 4);
                    const int i = (8 + 2 * hh + t) * 4;
                    a[2 * t] = pack2((akv[i] - s0.x * cs.x) * s0.y, (akv[i + 1] - s0.x * cs.y) * s0.y);
                    a[2 * t + 1] = pack2((akv[i + 2] - s1.x * cs.x) * s1.y, (akv[i + 3] - s1.x * cs.y) * s1.y);
                }
                stsm4(sb + OFF_VST + (hh >> 1) * 10240 + (hh & 1) * 4096 + stoff, a[0], a[1], a[2], a[3]);
                if (hh == 1) { wg_wait<1>(); if (elect) mbar_arrive(BAR(B_EQ + 0)); }
            }
            asm volatile("st.shared.v4.u32 [%0], {%1,%1,%1,%1};" :: "r"(sb + OFF_VST + wg * 10240 + 8192 + (tid & 127) * 16), "r"(0x3f803f80u) : "memory");
            wg_wait<0>(); if (elect) mbar_arrive(BAR(B_EQ + 1));
            fence_async_smem();
            bar_sync(1, 256);
            {
                float kvp[20];
                const uint64_t da = mkdesc(sb + OFF_PHI + wg * 16384, 128, 2048, 0), db = mkdesc(sb + OFF_VST + wg * 10240, 128, 2048, 0);
                wg_fence();
#pragma unroll
                for (int ks = 0; ks < 8; ks++) wgmma_n40_t11(kvp, da + ks * 16, db + ks * 16, ks != 0);
                wg_commit();
                wg_wait<0>();
                pin(kvp);
                float* dst = &g_kv[epoch & 1][(4 * j + 2 * wg + (w4 >> 1)) * KV_HEAD + (w4 & 1) * 16 + g];
#pragma unroll
                for (int t = 0; t < 2; t++)
#pragma unroll
                    for (int e = 0; e < 4; e++) {
                        float v = (w4 >= 2) ? kvp[8 + 4 * t + e] : kvp[4 * t + e];
                        red_f32(dst + (8 * t + 2 * c + (e & 1)) * KV_PITCH + (e >> 1) * 8, v);
                    }
                if (c == 0) { red_f32(dst + 16 * KV_PITCH, kvp[16]); red_f32(dst + 16 * KV_PITCH + 8, kvp[18]); }
                bar_sync(2 + wg, 128);
                if (elect) red_release(&g_f0[j * 32], 1);
            }
            STAMP(2);
#pragma unroll
            for (int q = 2; q < 4; q++) {
                mbar_wait(BAR(B_Q + q), 0);
                const uint64_t db = mkdesc(sb + OFF_SLOT + (3 + (q & 1)) * 16384, 8192, 1024, 1);
                wg_fence();
#pragma unroll
                for (int ks = 0; ks < 8; ks++) wgmma_n64_t01(aq, dxa + (2 * q + (ks >> 2)) * 1024 + (ks & 3) * 2, db + ks * 128, 1);
                wg_commit();
            }
            wg_wait<0>();
            pin(aq);
            if (elect) mbar_arrive(BAR(B_DQ));
#pragma unroll
            for (int hh = 0; hh < 4; hh++) {
                uint32_t a[4];
#pragma unroll
                for (int t = 0; t < 2; t++) {
                    const float2 cs = lds_f2(sb + OFF_CS + (128 + hh * 16 + t * 8 + 2 * c) * 4);
                    const int i = (2 * hh + t) * 4;
                    a[2 * t] = pack2((aq[i] - s0.x * cs.x) * s0.y, (aq[i + 1] - s0.x * cs.y) * s0.y);
                    a[2 * t + 1] = pack2((aq[i + 2] - s1.x * cs.x) * s1.y, (aq[i + 3] - s1.x * cs.y) * s1.y);
                }
                feature_map(a[0], a[1], a[2], a[3], &wb[hh * 4], &phq[hh * 8], &phq[hh * 8 + 4]);
            }
        }
        uint32_t hres[16];
        {
            const uint32_t* xp = (const uint32_t*)(P.x + (size_t)(64 * rh + 16 * w4 + g) * 512 + 128 * c4 + 64 * wg + 2 * c);
#pragma unroll
            for (int i = 0; i < 8; i++) { hres[2 * i] = __ldg(xp + 4 * i); hres[2 * i + 1] = __ldg(xp + 4 * i + 8 * 256); }
        }
        STAMP(3);
        {
            mbar_wait(BAR(B_KV), 0);
            STAMP(4);
            uint32_t* dst = g_obuf + ((2 * r + wg) * 64 + 8 * j) * 256 + 2 * w4 * 32 + lane;
#pragma unroll
            for (int hh = 0; hh < 4; hh++) {
                float n0[4] = {0, 0, 0, 0}, n1[4] = {0, 0, 0, 0}, dn[4] = {0, 0, 0, 0};
                const uint32_t kb = sb + OFF_KVS + hh * KV_HEAD * 4 + c * 8;
#pragma unroll
                for (int ks = 0; ks < 2; ks++) {
                    const uint32_t* a = &phq[hh * 8 + ks * 4];
                    float2 u, v;
                    u = lds_f2(kb + (g * KV_PITCH + 16 * ks) * 4); v = lds_f2(kb + (g * KV_PITCH + 16 * ks + 8) * 4);
                    mma16816(n0, a[0], a[1], a[2], a[3], pack2(u.x, u.y), pack2(v.x, v.y));
                    u = lds_f2(kb + ((g + 8) * KV_PITCH + 16 * ks) * 4); v = lds_f2(kb + ((g + 8) * KV_PITCH + 16 * ks + 8) * 4);
                    mma16816(n1, a[0], a[1], a[2], a[3], pack2(u.x, u.y), pack2(v.x, v.y));
                    u = lds_f2(kb + (16 * KV_PITCH + 16 * ks) * 4); v = lds_f2(kb + (16 * KV_PITCH + 16 * ks + 8) * 4);
                    mma16816(dn, a[0], a[1], a[2], a[3], pack2(u.x, u.y), pack2(v.x, v.y));
                }
                const float r0 = 1.f / (dn[0] + 1e-6f), r1 = 1.f / (dn[2] + 1e-6f);
                dst[(2 * hh) * 256] = pack2(n0[0] * r0, n0[1] * r0);
                dst[(2 * hh) * 256 + 32] = pack2(n0[2] * r1, n0[3] * r1);
                dst[(2 * hh + 1) * 256] = pack2(n1[0] * r0, n1[1] * r0);
                dst[(2 * hh + 1) * 256 + 32] = pack2(n1[2] * r1, n1[3] * r1);
            }
            bar_sync(2 + wg, 128);
            if (elect) st_release(&g_fo[(2 * r + wg) * 32 + j], epoch);
            STAMP(5);
        }
        {
            float acc[32];
            mbar_wait(BAR(B_WO), 0);
            const uint64_t da = mkdesc(sb + OFF_O, 1024, 128, 0), db = mkdesc(sb + OFF_X + wg * 65536, 8192, 1024, 1);
#pragma unroll
            for (int kb = 0; kb < 8; kb++) {
                mbar_wait(BAR(B_O + kb), 0);
                if (kb == 0) STAMP(6);
                wg_fence();
#pragma unroll
                for (int ks = 0; ks < 4; ks++) wgmma_n64_t01(acc, da + (kb * 4 + ks) * 128, db + (kb * 4 + ks) * 128, (kb | ks) != 0);
                wg_commit();
            }
            wg_wait<0>();
            pin(acc);
            if (elect) mbar_arrive(BAR(B_DA));
            STAMP(7);
            const int ct = 2 * c4 + wg;
            uint32_t* dst = g_hbuf + (rh * 64 + 8 * ct) * 256 + 2 * w4 * 32 + lane;
            float sa = 0, sbb = 0;
#pragma unroll
            for (int i = 0; i < 8; i++) {
                hres[2 * i] = pack2(lo_f(hres[2 * i]) + acc[4 * i], hi_f(hres[2 * i]) + acc[4 * i + 1]);
                hres[2 * i + 1] = pack2(lo_f(hres[2 * i + 1]) + acc[4 * i + 2], hi_f(hres[2 * i + 1]) + acc[4 * i + 3]);
                dst[i * 256] = hres[2 * i]; dst[i * 256 + 32] = hres[2 * i + 1];
                sa += lo_f(hres[2 * i]) + hi_f(hres[2 * i]); sbb += lo_f(hres[2 * i + 1]) + hi_f(hres[2 * i + 1]);
            }
            sa = quad_sum(sa) * (1.f / 64.f); sbb = quad_sum(sbb) * (1.f / 64.f);
            float ma = 0, mb = 0;
#pragma unroll
            for (int i = 0; i < 8; i++) {
                float d;
                d = lo_f(hres[2 * i]) - sa; ma = fmaf(d, d, ma); d = hi_f(hres[2 * i]) - sa; ma = fmaf(d, d, ma);
                d = lo_f(hres[2 * i + 1]) - sbb; mb = fmaf(d, d, mb); d = hi_f(hres[2 * i + 1]) - sbb; mb = fmaf(d, d, mb);
            }
            ma = quad_sum(ma); mb = quad_sum(mb);
            if (c == 0) {
                g_st2[(64 * rh + 16 * w4 + g) * 8 + ct] = make_float2(sa, ma);
                g_st2[(64 * rh + 16 * w4 + g + 8) * 8 + ct] = make_float2(sbb, mb);
            }
            bar_sync(2 + wg, 128);
            if (elect) st_release(&g_fh[rh * 32 + ct], epoch);
            STAMP(8);
        }
        uint32_t z1p[22];
        {
            float az2[44], az1[44];
            const uint64_t da = mkdesc(sb + OFF_X + wg * 65536, 1024, 128, 0);
#pragma unroll
            for (int kb = 0; kb < 8; kb++) {
                mbar_wait(BAR(B_WI + kb), 0);
                mbar_wait(BAR(B_H + wg * 8 + kb), 0);
                if (kb == 0) STAMP(9);
                const uint64_t db = mkdesc(sb + OFF_W + (kb % 7) * 12288, 4096, 512, 2);
                wg_fence();
#pragma unroll
                for (int ks = 0; ks < 4; ks++) wgmma_n88_t01(az2, da + (kb * 4 + ks) * 128, db + ks * 64, (kb | ks) != 0);
                wg_commit();
                if (kb >= 1) { wg_wait<1>(); if (elect) mbar_arrive(BAR(B_EI + kb - 1)); }
            }
#define Z1_BLOCK(kb) { \
                mbar_wait(BAR(B_WI + 8 + (kb)), 0); \
                const uint64_t db = mkdesc(sb + OFF_W + ((8 + (kb)) % 7) * 12288, 4096, 512, 2); \
                wg_fence(); \
                _Pragma("unroll") for (int ks = 0; ks < 4; ks++) wgmma_n88_t01(az1, da + ((kb) * 4 + ks) * 128, db + ks * 64, ((kb) | ks) != 0); \
                wg_commit(); }
            Z1_BLOCK(0)
            wg_wait<1>(); if (elect) mbar_arrive(BAR(B_EI + 7));
            pin(az2);
            STAMP(10);
            Z1_BLOCK(1) Z1_BLOCK(2) Z1_BLOCK(3)
            mbar_wait(BAR(B_AUX2), 0);
            const float2 s0 = lds_f2(sb + OFF_ST2 + (wg * 64 + w4 * 16 + g) * 8), s1 = lds_f2(sb + OFF_ST2 + (wg * 64 + w4 * 16 + g + 8) * 8);
            const int nvalid = (j == 7) ? 9 : 11;
            float sa = 0, sbb = 0;
#pragma unroll
            for (int i = 0; i < 11; i++) {
                const float2 cs = lds_f2(sb + OFF_CS + (192 + i * 8 + 2 * c) * 4);
                uint32_t p0 = pack2(gelu_tanh((az2[4 * i] - s0.x * cs.x) * s0.y), gelu_tanh((az2[4 * i + 1] - s0.x * cs.y) * s0.y));
                uint32_t p1 = pack2(gelu_tanh((az2[4 * i + 2] - s1.x * cs.x) * s1.y), gelu_tanh((az2[4 * i + 3] - s1.x * cs.y) * s1.y));
                az2[4 * i] = lo_f(p0); az2[4 * i + 1] = hi_f(p0); az2[4 * i + 2] = lo_f(p1); az2[4 * i + 3] = hi_f(p1);
                if (i < nvalid) { sa += az2[4 * i] + az2[4 * i + 1]; sbb += az2[4 * i + 2] + az2[4 * i + 3]; }
            }
            const float invn = 1.f / (8.f * nvalid);
            sa = quad_sum(sa) * invn; sbb = quad_sum(sbb) * invn;
            float ma = 0, mb = 0;
#pragma unroll
            for (int i = 0; i < 11; i++) {
                if (i < nvalid) {
                    float d;
                    d = az2[4 * i] - sa; ma = fmaf(d, d, ma); d = az2[4 * i + 1] - sa; ma = fmaf(d, d, ma);
                    d = az2[4 * i + 2] - sbb; mb = fmaf(d, d, mb); d = az2[4 * i + 3] - sbb; mb = fmaf(d, d, mb);
                }
            }
            ma = quad_sum(ma); mb = quad_sum(mb);
            const int row0 = 128 * r + 64 * wg + 16 * w4 + g;
            const unsigned long long tag = (unsigned long long)epoch << 32;
            if (c < 2) {
                float m = c ? sbb : sa, q2 = c ? mb : ma;
                asm volatile("st.relaxed.gpu.global.v2.u64 [%0], {%1,%2};" :: "l"(&g_st3[(row0 + 8 * c) * 16 + 2 * j]),
                             "l"(tag | __float_as_uint(m)), "l"(tag | __float_as_uint(q2)) : "memory");
            }
            STAMP(11);
            wg_wait<3>(); if (elect) mbar_arrive(BAR(B_EI + 8));
            Z1_BLOCK(4) Z1_BLOCK(5) Z1_BLOCK(6)
            float mu[2], rs[2];
            {
                unsigned long long w[2][4];
                int guard = 0;
                while (true) {
                    bool ok = true;
#pragma unroll
                    for (int rr = 0; rr < 2; rr++) {
                        const unsigned long long* p = &g_st3[(row0 + 8 * rr) * 16 + 4 * c];
                        asm volatile("ld.relaxed.gpu.global.v2.u64 {%0,%1}, [%2];" : "=l"(w[rr][0]), "=l"(w[rr][1]) : "l"(p) : "memory");
                        asm volatile("ld.relaxed.gpu.global.v2.u64 {%0,%1}, [%2];" : "=l"(w[rr][2]), "=l"(w[rr][3]) : "l"(p + 2) : "memory");
                    }
#pragma unroll
                    for (int rr = 0; rr < 2; rr++)
#pragma unroll
                        for (int e = 0; e < 4; e++) ok = ok && ((unsigned)(w[rr][e] >> 32) == epoch);
                    if (__all_sync(0xffffffffu, ok)) break;
                    if (++guard > SPIN_LIMIT) __trap();
                }
                const float n1 = (c == 3) ? 72.f : 88.f;
#pragma unroll
                for (int rr = 0; rr < 2; rr++) {
                    float m0 = __uint_as_float((unsigned)w[rr][0]), q0 = __uint_as_float((unsigned)w[rr][1]);
                    float m1 = __uint_as_float((unsigned)w[rr][2]), q1 = __uint_as_float((unsigned)w[rr][3]);
                    float m = quad_sum(m0 * 88.f + m1 * n1) * (1.f / 688.f);
                    float d0 = m0 - m, d1 = m1 - m;
                    float q = quad_sum(q0 + q1 + 88.f * d0 * d0 + n1 * d1 * d1);
                    mu[rr] = m; rs[rr] = rsqrtf(q * (1.f / 688.f) + 1e-5f);
                }
            }
            STAMP(12);
            {
                uint32_t* dst = g_zbuf + ((2 * r + wg) * 88 + 11 * j) * 256 + 2 * w4 * 32 + lane;
#pragma unroll
                for (int i = 0; i < 11; i++) {
                    const bool v = i < nvalid;
                    dst[i * 256] = v ? pack2((az2[4 * i] - mu[0]) * rs[0], (az2[4 * i + 1] - mu[0]) * rs[0]) : 0u;
                    dst[i * 256 + 32] = v ? pack2((az2[4 * i + 2] - mu[1]) * rs[1], (az2[4 * i + 3] - mu[1]) * rs[1]) : 0u;
                }
                bar_sync(2 + wg, 128);
                if (elect) st_release(&g_fz[(2 * r + wg) * 32 + j], epoch);
            }
            STAMP(13);
            Z1_BLOCK(7)
            wg_wait<0>();
            pin(az1);
            asm volatile("barrier.cluster.wait.acquire.aligned;" ::: "memory");
            if (elect) {
                mbar_arrive(BAR(B_DZ));
                asm volatile("{\n.reg .b32 ra;\nmapa.shared::cluster.u32 ra, %0, %1;\nmbarrier.arrive.release.cluster.shared::cluster.b64 _, [ra];\n}"
                             :: "r"(BAR(B_PR)), "r"(rank ^ 1) : "memory");
            }
#pragma unroll
            for (int i = 0; i < 11; i++) {
                const float2 cs = lds_f2(sb + OFF_CS + (280 + i * 8 + 2 * c) * 4);
                z1p[2 * i] = pack2(gelu_tanh((az1[4 * i] - s0.x * cs.x) * s0.y), gelu_tanh((az1[4 * i + 1] - s0.x * cs.y) * s0.y));
                z1p[2 * i + 1] = pack2(gelu_tanh((az1[4 * i + 2] - s1.x * cs.x) * s1.y), gelu_tanh((az1[4 * i + 3] - s1.x * cs.y) * s1.y));
            }
            STAMP(14);
        }
        {
            float acc[88];
            if (tid == 0) mbar_expect(BAR(B_XC), 45056);
#pragma unroll 1
            for (int it = 0; it < 16; it++) {
                const int s = it & 3;
                mbar_wait(BAR(B_F + s), (it >> 2) & 1);
                if (it == 0) STAMP(15);
                const uint64_t da = mkdesc(sb + s * P3_STAGE + wg * 8192, 16, 1024, 1), db = mkdesc(sb + s * P3_STAGE + 16384, 128, 1024, 0);
                wg_fence();
#pragma unroll
                for (int ks = 0; ks < 4; ks++) wgmma_n176_t01(acc, da + ks * 2, db + ks * 16, (it | ks) != 0);
                wg_commit();
                if (it >= 1) { wg_wait<1>(); if (elect) mbar_arrive(BAR(B_E + ((it - 1) & 3))); }
            }
            wg_wait<0>();
            pin(acc);
            if (elect) mbar_arrive(BAR(B_D3));
            STAMP(16);
            mbar_wait_cluster(BAR(B_PR), 0);
            uint32_t rdst, rbar;
            asm volatile("mapa.shared::cluster.u32 %0, %1, %2;" : "=r"(rdst) : "r"(sb + OFF_XC + tid * 16), "r"(rank ^ 1));
            asm volatile("mapa.shared::cluster.u32 %0, %1, %2;" : "=r"(rbar) : "r"(BAR(B_XC)), "r"(rank ^ 1));
            float keep[44];
#pragma unroll
            for (int i = 0; i < 11; i++) {
                float s0 = rank ? acc[4 * i] : acc[44 + 4 * i], s1 = rank ? acc[4 * i + 1] : acc[44 + 4 * i + 1];
                float s2 = rank ? acc[4 * i + 2] : acc[44 + 4 * i + 2], s3 = rank ? acc[4 * i + 3] : acc[44 + 4 * i + 3];
                asm volatile("st.async.weak.shared::cluster.mbarrier::complete_tx::bytes.v4.f32 [%0], {%1,%2,%3,%4}, [%5];"
                             :: "r"(rdst + i * 4096), "f"(s0), "f"(s1), "f"(s2), "f"(s3), "r"(rbar) : "memory");
#pragma unroll
                for (int e = 0; e < 4; e++) keep[4 * i + e] = rank ? acc[44 + 4 * i + e] : acc[4 * i + e];
            }
            const float b0 = lds_f(sb + OFF_BSP + (wg * 64 + w4 * 16 + g) * 4), b1 = lds_f(sb + OFF_BSP + (wg * 64 + w4 * 16 + g + 8) * 4);
            mbar_wait_cluster(BAR(B_XC), 0);
            STAMP(17);
            uint32_t* dst = g_ubuf + ((2 * r + wg) * 88 + 11 * j) * 256 + 2 * w4 * 32 + lane;
#pragma unroll
            for (int i = 0; i < 11; i++) {
                float4 o;
                asm volatile("ld.shared.v4.f32 {%0,%1,%2,%3}, [%4];" : "=f"(o.x), "=f"(o.y), "=f"(o.z), "=f"(o.w) : "r"(sb + OFF_XC + tid * 16 + i * 4096) : "memory");
                dst[i * 256] = pack2(lo_f(z1p[2 * i]) * (keep[4 * i] + o.x + b0), hi_f(z1p[2 * i]) * (keep[4 * i + 1] + o.y + b0));
                dst[i * 256 + 32] = pack2(lo_f(z1p[2 * i + 1]) * (keep[4 * i + 2] + o.z + b1), hi_f(z1p[2 * i + 1]) * (keep[4 * i + 3] + o.w + b1));
            }
            fence_async_smem();
            bar_sync(2 + wg, 128);
            if (elect) { mbar_arrive(BAR(B_DU)); st_release(&g_fu[(2 * r + wg) * 32 + j], epoch); }
            STAMP(18);
        }
        {
            float acc[32];
            const uint64_t da = mkdesc(sb + OFF_U, 1024, 128, 0);
#pragma unroll
            for (int b = 0; b < 11; b++) {
                mbar_wait(BAR(B_WT + b), 0);
                {
                    const int hi = (b == 10) ? 7 : (8 * b + 7) / 11;
                    const int lo = (b == 0) ? 0 : (8 * b - 1) / 11 + 1;
#pragma unroll
                    for (int t = 0; t < 8; t++) if (t >= lo && t <= hi) mbar_wait(BAR(B_U + t), 0);
                }
                if (b == 0) STAMP(19);
                const uint64_t db = mkdesc(sb + (b % 7) * 16384 + wg * 8192, 8192, 1024, 1);
                wg_fence();
#pragma unroll
                for (int ks = 0; ks < 4; ks++) if (b * 4 + ks < 43) wgmma_n64_t01(acc, da + (b * 4 + ks) * 128, db + ks * 128, (b | ks) != 0);
                wg_commit();
                if (b >= 1 && b <= 4) { wg_wait<1>(); if (elect) mbar_arrive(BAR(B_ET + b - 1)); }
            }
            wg_wait<0>();
            pin(acc);
            STAMP(20);
            uint32_t* op = (uint32_t*)(P.out + (size_t)(64 * rh + 16 * w4 + g) * 512 + 128 * c4 + 64 * wg + 2 * c);
#pragma unroll
            for (int i = 0; i < 8; i++) {
                op[4 * i] = pack2(lo_f(hres[2 * i]) + acc[4 * i], hi_f(hres[2 * i]) + acc[4 * i + 1]);
                op[4 * i + 8 * 256] = pack2(lo_f(hres[2 * i + 1]) + acc[4 * i + 2], hi_f(hres[2 * i + 1]) + acc[4 * i + 3]);
            }
            STAMP(21);
        }
    }
}

typedef CUresult (*EncodeFn)(CUtensorMap*, CUtensorMapDataType, cuuint32_t, void*, const cuuint64_t*, const cuuint64_t*, const cuuint32_t*,
                             const cuuint32_t*, CUtensorMapInterleave, CUtensorMapSwizzle, CUtensorMapL2promotion, CUtensorMapFloatOOBfill);

static void make_map(EncodeFn enc, CUtensorMap* m, const void* ptr, int rows, int cols, int box_rows, int box_cols, CUtensorMapSwizzle sw) {
    cuuint64_t gd[2] = {(cuuint64_t)cols, (cuuint64_t)rows};
    cuuint64_t gs[1] = {(cuuint64_t)cols * 2};
    cuuint32_t bx[2] = {(cuuint32_t)box_cols, (cuuint32_t)box_rows}, es[2] = {1, 1};
    enc(m, CU_TENSOR_MAP_DATA_TYPE_BFLOAT16, 2, (void*)ptr, gd, gs, bx, es, CU_TENSOR_MAP_INTERLEAVE_NONE, sw,
        CU_TENSOR_MAP_L2_PROMOTION_L2_256B, CU_TENSOR_MAP_FLOAT_OOB_FILL_NONE);
}

extern "C" void kernel_launch(void* const* d_in, const int* in_sizes, int n_in, void* d_out, int out_size) {
    static EncodeFn enc = nullptr;
    static int use_smid = 0;
    cudaLaunchConfig_t cfg = {};
    cudaLaunchAttribute at[1];
    at[0].id = cudaLaunchAttributeClusterDimension;
    at[0].val.clusterDim.x = 2; at[0].val.clusterDim.y = 1; at[0].val.clusterDim.z = 1;
    cfg.blockDim = dim3(384); cfg.dynamicSmemBytes = SMEM_BYTES; cfg.stream = cudaStreamPerThread;
    cfg.attrs = at; cfg.numAttrs = 1;
    if (!enc) {
        void* fn = nullptr; cudaDriverEntryPointQueryResult qr;
        cudaGetDriverEntryPoint("cuTensorMapEncodeTiled", &fn, cudaEnableDefault, &qr);
        enc = (EncodeFn)fn;
        cudaFuncSetAttribute(fused_kernel, cudaFuncAttributeMaxDynamicSharedMemorySize, SMEM_BYTES);
        int nsm = 0, ncl = 0;
        cudaDeviceGetAttribute(&nsm, cudaDevAttrMultiProcessorCount, 0);
        cfg.gridDim = dim3(132);
        cudaOccupancyMaxActiveClusters(&ncl, fused_kernel, &cfg);
        use_smid = (nsm == 132 && ncl == 66);
    }
    Params P;
    P.x = (const bf16*)d_in[0]; P.wqkv = (const bf16*)d_in[1]; P.wphi = (const bf16*)d_in[2]; P.wo = (const bf16*)d_in[3];
    P.win = (const bf16*)d_in[5]; P.wsp = (const bf16*)d_in[6]; P.bsp = (const bf16*)d_in[7]; P.wout = (const bf16*)d_in[8];
    P.out = (bf16*)d_out;
    P.use_smid = use_smid;
    make_map(enc, &P.mx, P.x, 2048, 512, 128, 64, CU_TENSOR_MAP_SWIZZLE_128B);
    make_map(enc, &P.mwqkv, P.wqkv, 512, 1536, 64, 64, CU_TENSOR_MAP_SWIZZLE_128B);
    make_map(enc, &P.mwo, P.wo, 512, 512, 256, 64, CU_TENSOR_MAP_SWIZZLE_128B);
    make_map(enc, &P.mwin, P.win, 512, 1376, 64, 32, CU_TENSOR_MAP_SWIZZLE_64B);
    make_map(enc, &P.mwsp, P.wsp, 2048, 2048, 128, 64, CU_TENSOR_MAP_SWIZZLE_128B);
    make_map(enc, &P.mwout, P.wout, 688, 512, 64, 64, CU_TENSOR_MAP_SWIZZLE_128B);
    cfg.gridDim = dim3(use_smid ? 132 : 128);
    cudaLaunchKernelEx(&cfg, fused_kernel, P);
}
```

```cpp
#include <cuda_runtime.h>
#include <cuda.h>
#include <cuda_bf16.h>
#include <stdint.h>
#include <stdlib.h>

typedef __nv_bfloat16 bf16;

__device__ __forceinline__ void wgmma_n128_t01(float (&d)[64], uint64_t da, uint64_t db, int sd) {
  asm volatile("{\n.reg .pred p;\nsetp.ne.b32 p, %66, 0;\n"
    "wgmma.mma_async.sync.aligned.m64n128k16.f32.bf16.bf16 {%0, %1, %2, %3, %4, %5, %6, %7, %8, %9, %10, %11, %12, %13, %14, %15, %16, %17, %18, %19, %20, %21, %22, %23, %24, %25, %26, %27, %28, %29, %30, %31, %32, %33, %34, %35, %36, %37, %38, %39, %40, %41, %42, %43, %44, %45, %46, %47, %48, %49, %50, %51, %52, %53, %54, %55, %56, %57, %58, %59, %60, %61, %62, %63}, %64, %65, p, 1, 1, 0, 1;\n}\n"
    : "+f"(d[0]), "+f"(d[1]), "+f"(d[2]), "+f"(d[3]), "+f"(d[4]), "+f"(d[5]), "+f"(d[6]), "+f"(d[7]), "+f"(d[8]), "+f"(d[9]), "+f"(d[10]), "+f"(d[11]), "+f"(d[12]), "+f"(d[13]), "+f"(d[14]), "+f"(d[15]), "+f"(d[16]), "+f"(d[17]), "+f"(d[18]), "+f"(d[19]), "+f"(d[20]), "+f"(d[21]), "+f"(d[22]), "+f"(d[23]), "+f"(d[24]), "+f"(d[25]), "+f"(d[26]), "+f"(d[27]), "+f"(d[28]), "+f"(d[29]), "+f"(d[30]), "+f"(d[31]), "+f"(d[32]), "+f"(d[33]), "+f"(d[34]), "+f"(d[35]), "+f"(d[36]), "+f"(d[37]), "+f"(d[38]), "+f"(d[39]), "+f"(d[40]), "+f"(d[41]), "+f"(d[42]), "+f"(d[43]), "+f"(d[44]), "+f"(d[45]), "+f"(d[46]), "+f"(d[47]), "+f"(d[48]), "+f"(d[49]), "+f"(d[50]), "+f"(d[51]), "+f"(d[52]), "+f"(d[53]), "+f"(d[54]), "+f"(d[55]), "+f"(d[56]), "+f"(d[57]), "+f"(d[58]), "+f"(d[59]), "+f"(d[60]), "+f"(d[61]), "+f"(d[62]), "+f"(d[63])
    : "l"(da), "l"(db), "r"(sd));
}
__device__ __forceinline__ void wgmma_n64_t01(float (&d)[32], uint64_t da, uint64_t db, int sd) {
  asm volatile("{\n.reg .pred p;\nsetp.ne.b32 p, %34, 0;\n"
    "wgmma.mma_async.sync.aligned.m64n64k16.f32.bf16.bf16 {%0, %1, %2, %3, %4, %5, %6, %7, %8, %9, %10, %11, %12, %13, %14, %15, %16, %17, %18, %19, %20, %21, %22, %23, %24, %25, %26, %27, %28, %29, %30, %31}, %32, %33, p, 1, 1, 0, 1;\n}\n"
    : "+f"(d[0]), "+f"(d[1]), "+f"(d[2]), "+f"(d[3]), "+f"(d[4]), "+f"(d[5]), "+f"(d[6]), "+f"(d[7]), "+f"(d[8]), "+f"(d[9]), "+f"(d[10]), "+f"(d[11]), "+f"(d[12]), "+f"(d[13]), "+f"(d[14]), "+f"(d[15]), "+f"(d[16]), "+f"(d[17]), "+f"(d[18]), "+f"(d[19]), "+f"(d[20]), "+f"(d[21]), "+f"(d[22]), "+f"(d[23]), "+f"(d[24]), "+f"(d[25]), "+f"(d[26]), "+f"(d[27]), "+f"(d[28]), "+f"(d[29]), "+f"(d[30]), "+f"(d[31])
    : "l"(da), "l"(db), "r"(sd));
}
__device__ __forceinline__ void wgmma_n88_t01(float (&d)[44], uint64_t da, uint64_t db, int sd) {
  asm volatile("{\n.reg .pred p;\nsetp.ne.b32 p, %46, 0;\n"
    "wgmma.mma_async.sync.aligned.m64n88k16.f32.bf16.bf16 {%0, %1, %2, %3, %4, %5, %6, %7, %8, %9, %10, %11, %12, %13, %14, %15, %16, %17, %18, %19, %20, %21, %22, %23, %24, %25, %26, %27, %28, %29, %30, %31, %32, %33, %34, %35, %36, %37, %38, %39, %40, %41, %42, %43}, %44, %45, p, 1, 1, 0, 1;\n}\n"
    : "+f"(d[0]), "+f"(d[1]), "+f"(d[2]), "+f"(d[3]), "+f"(d[4]), "+f"(d[5]), "+f"(d[6]), "+f"(d[7]), "+f"(d[8]), "+f"(d[9]), "+f"(d[10]), "+f"(d[11]), "+f"(d[12]), "+f"(d[13]), "+f"(d[14]), "+f"(d[15]), "+f"(d[16]), "+f"(d[17]), "+f"(d[18]), "+f"(d[19]), "+f"(d[20]), "+f"(d[21]), "+f"(d[22]), "+f"(d[23]), "+f"(d[24]), "+f"(d[25]), "+f"(d[26]), "+f"(d[27]), "+f"(d[28]), "+f"(d[29]), "+f"(d[30]), "+f"(d[31]), "+f"(d[32]), "+f"(d[33]), "+f"(d[34]), "+f"(d[35]), "+f"(d[36]), "+f"(d[37]), "+f"(d[38]), "+f"(d[39]), "+f"(d[40]), "+f"(d[41]), "+f"(d[42]), "+f"(d[43])
    : "l"(da), "l"(db), "r"(sd));
}
__device__ __forceinline__ void wgmma_n64_t11(float (&d)[32], uint64_t da, uint64_t db, int sd) {
  asm volatile("{\n.reg .pred p;\nsetp.ne.b32 p, %34, 0;\n"
    "wgmma.mma_async.sync.aligned.m64n64k16.f32.bf16.bf16 {%0, %1, %2, %3, %4, %5, %6, %7, %8, %9, %10, %11, %12, %13, %14, %15, %16, %17, %18, %19, %20, %21, %22, %23, %24, %25, %26, %27, %28, %29, %30, %31}, %32, %33, p, 1, 1, 1, 1;\n}\n"
    : "+f"(d[0]), "+f"(d[1]), "+f"(d[2]), "+f"(d[3]), "+f"(d[4]), "+f"(d[5]), "+f"(d[6]), "+f"(d[7]), "+f"(d[8]), "+f"(d[9]), "+f"(d[10]), "+f"(d[11]), "+f"(d[12]), "+f"(d[13]), "+f"(d[14]), "+f"(d[15]), "+f"(d[16]), "+f"(d[17]), "+f"(d[18]), "+f"(d[19]), "+f"(d[20]), "+f"(d[21]), "+f"(d[22]), "+f"(d[23]), "+f"(d[24]), "+f"(d[25]), "+f"(d[26]), "+f"(d[27]), "+f"(d[28]), "+f"(d[29]), "+f"(d[30]), "+f"(d[31])
    : "l"(da), "l"(db), "r"(sd));
}

__device__ __forceinline__ void wgmma_n176_t01(float (&d)[44], float (&e)[44], uint64_t da, uint64_t db, int sd) {
  asm volatile("{\n.reg .pred p;\nsetp.ne.b32 p, %90, 0;\n"
    "wgmma.mma_async.sync.aligned.m64n176k16.f32.bf16.bf16 {%0, %1, %2, %3, %4, %5, %6, %7, %8, %9, %10, %11, %12, %13, %14, %15, %16, %17, %18, %19, %20, %21, %22, %23, %24, %25, %26, %27, %28, %29, %30, %31, %32, %33, %34, %35, %36, %37, %38, %39, %40, %41, %42, %43, %44, %45, %46, %47, %48, %49, %50, %51, %52, %53, %54, %55, %56, %57, %58, %59, %60, %61, %62, %63, %64, %65, %66, %67, %68, %69, %70, %71, %72, %73, %74, %75, %76, %77, %78, %79, %80, %81, %82, %83, %84, %85, %86, %87}, %88, %89, p, 1, 1, 0, 1;\n}\n"
    : "+f"(d[0]), "+f"(d[1]), "+f"(d[2]), "+f"(d[3]), "+f"(d[4]), "+f"(d[5]), "+f"(d[6]), "+f"(d[7]), "+f"(d[8]), "+f"(d[9]), "+f"(d[10]), "+f"(d[11]), "+f"(d[12]), "+f"(d[13]), "+f"(d[14]), "+f"(d[15]), "+f"(d[16]), "+f"(d[17]), "+f"(d[18]), "+f"(d[19]), "+f"(d[20]), "+f"(d[21]), "+f"(d[22]), "+f"(d[23]), "+f"(d[24]), "+f"(d[25]), "+f"(d[26]), "+f"(d[27]), "+f"(d[28]), "+f"(d[29]), "+f"(d[30]), "+f"(d[31]), "+f"(d[32]), "+f"(d[33]), "+f"(d[34]), "+f"(d[35]), "+f"(d[36]), "+f"(d[37]), "+f"(d[38]), "+f"(d[39]), "+f"(d[40]), "+f"(d[41]), "+f"(d[42]), "+f"(d[43]), "+f"(e[0]), "+f"(e[1]), "+f"(e[2]), "+f"(e[3]), "+f"(e[4]), "+f"(e[5]), "+f"(e[6]), "+f"(e[7]), "+f"(e[8]), "+f"(e[9]), "+f"(e[10]), "+f"(e[11]), "+f"(e[12]), "+f"(e[13]), "+f"(e[14]), "+f"(e[15]), "+f"(e[16]), "+f"(e[17]), "+f"(e[18]), "+f"(e[19]), "+f"(e[20]), "+f"(e[21]), "+f"(e[22]), "+f"(e[23]), "+f"(e[24]), "+f"(e[25]), "+f"(e[26]), "+f"(e[27]), "+f"(e[28]), "+f"(e[29]), "+f"(e[30]), "+f"(e[31]), "+f"(e[32]), "+f"(e[33]), "+f"(e[34]), "+f"(e[35]), "+f"(e[36]), "+f"(e[37]), "+f"(e[38]), "+f"(e[39]), "+f"(e[40]), "+f"(e[41]), "+f"(e[42]), "+f"(e[43])
    : "l"(da), "l"(db), "r"(sd));
}

#define KV_HEAD 544
struct alignas(1024) Scratch {
    unsigned f0[8 * 96];
    unsigned pad0[256];
    unsigned ep[136 * 32];
    unsigned fo[32 * 32], fh[32 * 32], fz[32 * 32], fu[32 * 32];
    uint2 st1[2048];
    float2 st2[2048 * 8];
    uint4 st3[8 * 1024];
    float cs[8 * 16 * 384];
    float kv[32 * KV_HEAD];
    uint4 wpk[8 * 2 * 8 * 704];
    uint32_t obuf[32 * 64 * 256], hbuf[32 * 64 * 256], ubuf[32 * 88 * 256], zbuf[32 * 88 * 256];
};
__device__ Scratch g_scr;
#define YSTAMP(i)
#define GSTAMP(i)
#define STAMP(i)
#define XSTAMP(i)

struct alignas(64) Params { CUtensorMap mx, mwqkv, mw32, mwo, mwsp, mwout, mout; };

constexpr uint32_t OFF_X = 0;
constexpr uint32_t OFF_W = 131072;
constexpr uint32_t OFF_MISC = 131072 + 90112;
constexpr uint32_t OFF_ST1 = OFF_MISC;
constexpr uint32_t OFF_ST2 = OFF_MISC + 1024;
constexpr uint32_t OFF_CS = OFF_MISC + 2048;
constexpr uint32_t OFF_BSP = OFF_MISC + 3584;
constexpr uint32_t OFF_EP = OFF_MISC + 4096;
constexpr uint32_t OFF_BAR = OFF_MISC + 4224;
constexpr uint32_t OFF_WB = OFF_BAR + 1280;
constexpr uint32_t SMEM_USED = OFF_WB + 2048;
constexpr uint32_t SMEM_BYTES = SMEM_USED + 1024;
constexpr uint32_t OFF_SLOT = OFF_W + 4096;
constexpr uint32_t OFF_SX = OFF_X + 6 * 16384;
constexpr uint32_t OFF_PHI = OFF_W;
constexpr uint32_t OFF_VST = OFF_W + 32768;
constexpr uint32_t OFF_KVS = OFF_W;
constexpr uint32_t OFF_O = OFF_W + 20480;
#define P3_A(s) (((s) & 1) * 16384 + ((s) >> 1) * 65536)
#define P3_B(s) ((s) < 2 ? OFF_W + (s) * 22528 : (s) == 2 ? 32768 : 98304)
#define P3_KB(it) (2 * ((it) == 0 ? r : ((it) <= r ? (it) - 1 : (it))) + (int)rank)
constexpr uint32_t OFF_XC = OFF_W + 45056;
#define P3_WT(b) (((b) >= 6 ? (b) - 6 : (b) + 1) * 16384)
constexpr uint32_t OFF_U = OFF_MISC - 90112;

enum {
    B_X = 0, B_ST = 9, B_W = 8, B_Q = 16, B_KV = 20, B_WO = 21, B_O = 22, B_H = 30, B_WI = 46, B_XC = 62, B_WT = 63, B_U = 75,
    B_F = 83, B_LO = 87, B_LH = 89, B_LU = 93,
    B_EW = 96, B_EQ = 101, B_EI = 105, B_DZ = 113, B_ET = 114, B_E = 119, B_ZH = 123, B_LZ = 124, B_PR = 129, B_END = 130, B_EO = 131,
    B_AUX1 = 144, B_AUX2 = 145
};

__device__ __forceinline__ uint32_t smem_u32(const void* p) { return (uint32_t)__cvta_generic_to_shared(p); }
__device__ __forceinline__ void mbar_init(uint32_t bar, int cnt) { asm volatile("mbarrier.init.shared::cta.b64 [%0], %1;" :: "r"(bar), "r"(cnt) : "memory"); }
__device__ __forceinline__ void mbar_expect(uint32_t bar, uint32_t bytes) { asm volatile("mbarrier.arrive.expect_tx.shared::cta.b64 _, [%0], %1;" :: "r"(bar), "r"(bytes) : "memory"); }
__device__ __forceinline__ void mbar_arrive(uint32_t bar) { asm volatile("mbarrier.arrive.shared::cta.b64 _, [%0];" :: "r"(bar) : "memory"); }
__device__ __forceinline__ void mbar_wait(uint32_t bar, uint32_t parity) {
    asm volatile("{\n.reg .pred p;\nW_%=:\nmbarrier.try_wait.parity.shared::cta.b64 p, [%0], %1;\n@!p bra W_%=;\n}" :: "r"(bar), "r"(parity) : "memory");
}
__device__ __forceinline__ void mbar_wait_cluster(uint32_t bar, uint32_t parity) {
    asm volatile("{\n.reg .pred p;\nW_%=:\nmbarrier.try_wait.parity.acquire.cluster.shared::cta.b64 p, [%0], %1;\n@!p bra W_%=;\n}" :: "r"(bar), "r"(parity) : "memory");
}
__device__ __forceinline__ void mbar_wait_watchdog(uint32_t bar) {
    uint32_t ok; long long t0 = clock64();
    while (true) {
        asm volatile("{\n.reg .pred p;\nmbarrier.try_wait.parity.shared::cta.b64 p, [%1], 0;\nselp.u32 %0, 1, 0, p;\n}" : "=r"(ok) : "r"(bar) : "memory");
        if (ok) break;
        if (clock64() - t0 > 400000000ll) __trap();
        __nanosleep(64);
    }
}
__device__ __forceinline__ void mbar_arrive_cluster(uint32_t bar, uint32_t cta) {
    asm volatile("{\n.reg .b32 ra;\nmapa.shared::cluster.u32 ra, %0, %1;\nmbarrier.arrive.shared::cluster.b64 _, [ra];\n}" :: "r"(bar), "r"(cta) : "memory");
}
__device__ __forceinline__ void tma2d(uint32_t dst, const CUtensorMap* m, int c0, int c1, uint32_t bar) {
    asm volatile("cp.async.bulk.tensor.2d.shared::cluster.global.mbarrier::complete_tx::bytes [%0], [%1, {%3, %4}], [%2];"
                 :: "r"(dst), "l"(m), "r"(bar), "r"(c0), "r"(c1) : "memory");
}
__device__ __forceinline__ void bulk1d(uint32_t dst, const void* src, uint32_t bytes, uint32_t bar) {
    asm volatile("cp.async.bulk.shared::cluster.global.mbarrier::complete_tx::bytes [%0], [%1], %2, [%3];"
                 :: "r"(dst), "l"(src), "r"(bytes), "r"(bar) : "memory");
}
__device__ __forceinline__ void l2_prefetch(const void* src, uint32_t bytes) {
    asm volatile("cp.async.bulk.prefetch.L2.global [%0], %1;" :: "l"(src), "r"(bytes) : "memory");
}
__device__ __forceinline__ unsigned ld_acquire(const unsigned* p) { unsigned v; asm volatile("ld.acquire.gpu.global.u32 %0, [%1];" : "=r"(v) : "l"(p) : "memory"); return v; }
__device__ __forceinline__ unsigned ld_relaxed(const unsigned* p) { unsigned v; asm volatile("ld.relaxed.gpu.global.u32 %0, [%1];" : "=r"(v) : "l"(p) : "memory"); return v; }
__device__ __forceinline__ void st_release(unsigned* p, unsigned v) { asm volatile("st.release.gpu.global.u32 [%0], %1;" :: "l"(p), "r"(v) : "memory"); }
__device__ __forceinline__ void red_release(unsigned* p, unsigned v) { asm volatile("red.release.gpu.global.add.u32 [%0], %1;" :: "l"(p), "r"(v) : "memory"); }
__device__ __forceinline__ void red_f32x4(float* p, float a, float b, float c, float d) {
    asm volatile("red.relaxed.gpu.global.add.v4.f32 [%0], {%1,%2,%3,%4};" :: "l"(p), "f"(a), "f"(b), "f"(c), "f"(d) : "memory");
}
__device__ __forceinline__ void wait_flag(const unsigned* p, unsigned target) {
    while ((int)(ld_acquire(p) - target) < 0) {}
}
__device__ __forceinline__ void fence_async_global() { asm volatile("fence.proxy.async.global;" ::: "memory"); }
__device__ __forceinline__ void fence_async_smem() { asm volatile("fence.proxy.async.shared::cta;" ::: "memory"); }
__device__ __forceinline__ void bar_sync(int id, int n) { asm volatile("bar.sync %0, %1;" :: "r"(id), "r"(n) : "memory"); }
__device__ __forceinline__ void wg_fence() { asm volatile("wgmma.fence.sync.aligned;" ::: "memory"); }
__device__ __forceinline__ void wg_commit() { asm volatile("wgmma.commit_group.sync.aligned;" ::: "memory"); }
template <int N> __device__ __forceinline__ void wg_wait() { asm volatile("wgmma.wait_group.sync.aligned %0;" :: "n"(N) : "memory"); }
template <int N> __device__ __forceinline__ void pin(float (&d)[N]) {
#pragma unroll
    for (int i = 0; i < N; i++) asm volatile("" : "+f"(d[i]) :: "memory");
}
__device__ __forceinline__ uint64_t mkdesc(uint32_t addr, uint32_t lbo, uint32_t sbo, uint32_t layout) {
    return (uint64_t)((addr & 0x3FFFF) >> 4) | ((uint64_t)(lbo >> 4) << 16) | ((uint64_t)(sbo >> 4) << 32) | ((uint64_t)layout << 62);
}
__device__ __forceinline__ uint32_t pack2(float lo, float hi) { uint32_t r; asm("cvt.rn.bf16x2.f32 %0, %1, %2;" : "=r"(r) : "f"(hi), "f"(lo)); return r; }
__device__ __forceinline__ float lo_f(uint32_t w) { return __uint_as_float(w << 16); }
__device__ __forceinline__ float hi_f(uint32_t w) { return __uint_as_float(w & 0xffff0000u); }
__device__ __forceinline__ float ex2(float x) { float r; asm("ex2.approx.ftz.f32 %0, %1;" : "=f"(r) : "f"(x)); return r; }
__device__ __forceinline__ float rcp(float x) { float r; asm("rcp.approx.ftz.f32 %0, %1;" : "=f"(r) : "f"(x)); return r; }
__device__ __forceinline__ float rsq(float x) { float r; asm("rsqrt.approx.ftz.f32 %0, %1;" : "=f"(r) : "f"(x)); return r; }
__device__ __forceinline__ float gelu_half(float hv) {
    float u = hv * fmaf(hv * hv, 0.285419265090401f, 1.5957691216057308f);
    float t; asm("tanh.approx.f32 %0, %1;" : "=f"(t) : "f"(u));
    return fmaf(hv, t, hv);
}
__device__ __forceinline__ void stsm4(uint32_t addr, uint32_t r0, uint32_t r1, uint32_t r2, uint32_t r3) {
    asm volatile("stmatrix.sync.aligned.m8n8.x4.shared.b16 [%0], {%1,%2,%3,%4};" :: "r"(addr), "r"(r0), "r"(r1), "r"(r2), "r"(r3) : "memory");
}
__device__ __forceinline__ void sts_f2(uint32_t a, float x, float y) { asm volatile("st.shared.v2.f32 [%0], {%1,%2};" :: "r"(a), "f"(x), "f"(y) : "memory"); }
__device__ __forceinline__ uint32_t tagf(float v, unsigned epoch) { return (__float_as_uint(v) & ~3u) | (epoch & 3u); }
__device__ __forceinline__ uint4 ld_relaxed4(const void* p) {
    uint4 v; asm volatile("ld.relaxed.gpu.global.v4.u32 {%0,%1,%2,%3}, [%4];" : "=r"(v.x), "=r"(v.y), "=r"(v.z), "=r"(v.w) : "l"(p) : "memory"); return v;
}
__device__ __forceinline__ float quad_sum(float v) { v += __shfl_xor_sync(0xffffffffu, v, 1); v += __shfl_xor_sync(0xffffffffu, v, 2); return v; }
__device__ __forceinline__ float quad_reduce4(float v0, float v1, float v2, float v3, int c) {
    const bool up = c & 2, odd = c & 1;
    const float a = (up ? v2 : v0) + __shfl_xor_sync(0xffffffffu, up ? v0 : v2, 2);
    const float b = (up ? v3 : v1) + __shfl_xor_sync(0xffffffffu, up ? v1 : v3, 2);
    return (odd ? b : a) + __shfl_xor_sync(0xffffffffu, odd ? a : b, 1);
}
__device__ __forceinline__ void st_relaxed(uint32_t* p, uint32_t v) { asm volatile("st.relaxed.gpu.global.u32 [%0], %1;" :: "l"(p), "r"(v) : "memory"); }
__device__ __forceinline__ float colsum8(const uint4* cw, int lane) {
    float s[8];
    s[0] = lo_f(cw[0].x); s[1] = hi_f(cw[0].x); s[2] = lo_f(cw[0].y); s[3] = hi_f(cw[0].y);
    s[4] = lo_f(cw[0].z); s[5] = hi_f(cw[0].z); s[6] = lo_f(cw[0].w); s[7] = hi_f(cw[0].w);
#pragma unroll
    for (int q = 1; q < 4; q++) {
        s[0] += lo_f(cw[q].x); s[1] += hi_f(cw[q].x); s[2] += lo_f(cw[q].y); s[3] += hi_f(cw[q].y);
        s[4] += lo_f(cw[q].z); s[5] += hi_f(cw[q].z); s[6] += lo_f(cw[q].w); s[7] += hi_f(cw[q].w);
    }
#pragma unroll
    for (int q = 0; q < 4; q++) { const bool up = lane & 4; float t = __shfl_xor_sync(0xffffffffu, up ? s[q] : s[q + 4], 4); s[q] = (up ? s[q + 4] : s[q]) + t; }
#pragma unroll
    for (int q = 0; q < 2; q++) { const bool up = lane & 2; float t = __shfl_xor_sync(0xffffffffu, up ? s[q] : s[q + 2], 2); s[q] = (up ? s[q + 2] : s[q]) + t; }
    const bool up = lane & 1;
    return (up ? s[1] : s[0]) + __shfl_xor_sync(0xffffffffu, up ? s[0] : s[1], 1);
}

#define POLL_ISSUE(NL, FLAGPTR, ISSUE) { \
        bool done_ = lane >= (NL) || (SKIPLOCAL && (lane & 7) < 2); const unsigned* fp_ = (FLAGPTR); \
        while (true) { \
            if (!done_ && (int)(ld_acquire(fp_) - epoch) >= 0) { fence_async_global(); ISSUE; done_ = true; } \
            if (__all_sync(0xffffffffu, done_)) break; \
        } }

template <bool NORM>
__device__ __forceinline__ void feature_map4(const float (&p)[32], uint32_t (&o)[32]) {
    const float L2E = 1.4426950408889634f;
    float mx[8], mn[8];
#pragma unroll
    for (int i = 0; i < 8; i++) {
        const float* q = &p[(i >> 1) * 8 + (i & 1) * 2];
        mx[i] = fmaxf(fmaxf(q[0], q[1]), fmaxf(q[4], q[5]));
        mn[i] = fminf(fminf(q[0], q[1]), fminf(q[4], q[5]));
    }
#pragma unroll
    for (int d = 1; d <= 2; d <<= 1) {
        float a[8], b[8];
#pragma unroll
        for (int i = 0; i < 8; i++) { a[i] = __shfl_xor_sync(0xffffffffu, mx[i], d); b[i] = __shfl_xor_sync(0xffffffffu, mn[i], d); }
#pragma unroll
        for (int i = 0; i < 8; i++) { mx[i] = fmaxf(mx[i], a[i]); mn[i] = fminf(mn[i], b[i]); }
    }
    float e[64], s[16];
#pragma unroll
    for (int i = 0; i < 8; i++) {
        const float* q = &p[(i >> 1) * 8 + (i & 1) * 2];
        const float a = -L2E * mx[i], b = L2E * mn[i];
        float* u = &e[8 * i];
        u[0] = ex2(fmaf(q[0], L2E, a)); u[1] = ex2(fmaf(q[1], L2E, a)); u[2] = ex2(fmaf(q[4], L2E, a)); u[3] = ex2(fmaf(q[5], L2E, a));
        u[4] = ex2(fmaf(q[0], -L2E, b)); u[5] = ex2(fmaf(q[1], -L2E, b)); u[6] = ex2(fmaf(q[4], -L2E, b)); u[7] = ex2(fmaf(q[5], -L2E, b));
    }
    if (!NORM) {
#pragma unroll
        for (int i = 0; i < 8; i++) {
            const float* u = &e[8 * i];
            uint32_t* w = &o[(i >> 1) * 8 + (i & 1)];
            w[0] = pack2(u[0], u[1]); w[2] = pack2(u[2], u[3]); w[4] = pack2(u[4], u[5]); w[6] = pack2(u[6], u[7]);
        }
        return;
    }
#pragma unroll
    for (int i = 0; i < 8; i++) { const float* u = &e[8 * i]; s[2 * i] = (u[0] + u[1]) + (u[2] + u[3]); s[2 * i + 1] = (u[4] + u[5]) + (u[6] + u[7]); }
#pragma unroll
    for (int d = 1; d <= 2; d <<= 1) {
        float a[16];
#pragma unroll
        for (int k = 0; k < 16; k++) a[k] = __shfl_xor_sync(0xffffffffu, s[k], d);
#pragma unroll
        for (int k = 0; k < 16; k++) s[k] += a[k];
    }
#pragma unroll
    for (int i = 0; i < 8; i++) {
        const float a = rcp(s[2 * i]), b = rcp(s[2 * i + 1]);
        const float* u = &e[8 * i];
        uint32_t* w = &o[(i >> 1) * 8 + (i & 1)];
        w[0] = pack2(u[0] * a, u[1] * a); w[2] = pack2(u[2] * a, u[3] * a);
        w[4] = pack2(u[4] * b, u[5] * b); w[6] = pack2(u[6] * b, u[7] * b);
    }
}
__device__ __forceinline__ void mma16816z(float* c, const uint32_t* a, uint32_t b0, uint32_t b1) {
    asm("mma.sync.aligned.m16n8k16.row.col.f32.bf16.bf16.f32 {%0,%1,%2,%3}, {%4,%5,%6,%7}, {%8,%9}, {%10,%10,%10,%10};"
                 : "=f"(c[0]), "=f"(c[1]), "=f"(c[2]), "=f"(c[3]) : "r"(a[0]), "r"(a[1]), "r"(a[2]), "r"(a[3]), "r"(b0), "r"(b1), "f"(0.f));
}

__device__ __forceinline__ int pair_from_tpc(int t) {
    int g, slot;
    if (t < 32) { g = t & 7; slot = t >> 3; }
    else if (t < 60) { g = 1 + (t - 32) % 7; slot = 4 + (t - 32) / 7; }
    else if (t < 62) return -1;
    else { g = 0; slot = 4 + (t - 62); }
    return g * 8 + slot;
}

#define SKB 2
#define ZSPLIT 0
#define GSLEEP 300
#define SBOTH 1
#define PACE 3
template <bool USE_SMID>
__global__ void __launch_bounds__(384, 1) fused_kernel(const bf16* __restrict__ p_x, Scratch* __restrict__ S, const bf16* __restrict__ p_wphi, const bf16* __restrict__ p_bsp,
             const bf16* __restrict__ p_win, const bf16* __restrict__ p_wout, const __grid_constant__ Params P) {
    extern __shared__ __align__(1024) uint8_t smem_raw[];
    const uint32_t sb = (smem_u32(smem_raw) + 1023) & ~1023u;
    uint8_t* sp = smem_raw + (sb - smem_u32(smem_raw));
#define SF2(off) (*(const float2*)(sp + (off)))
    const int tid = threadIdx.x, lane = tid & 31;
    const int warp = __shfl_sync(0xffffffffu, tid >> 5, 0);
    if (tid == 0) {
        asm volatile("prefetch.tensormap [%0];" :: "l"(&P.mw32) : "memory");
        asm volatile("prefetch.tensormap [%0];" :: "l"(&P.mx) : "memory");
        asm volatile("prefetch.tensormap [%0];" :: "l"(&P.mwqkv) : "memory");
    }
    uint32_t rank; asm volatile("mov.u32 %0, %%cluster_ctarank;" : "=r"(rank));
    int pair;
    if (USE_SMID) { uint32_t smid; asm volatile("mov.u32 %0, %%smid;" : "=r"(smid)); pair = pair_from_tpc(smid >> 1); }
    else pair = blockIdx.x >> 1;
    if (pair < 0) {
        if (tid < 8) {
            uint32_t smid; asm volatile("mov.u32 %0, %%smid;" : "=r"(smid));
            unsigned* ep = &S->ep[(128 + (smid & 3)) * 32];
            const unsigned e = __ldcg(ep) + 1u;
            int guard = 0;
            do { __nanosleep(1000); } while ((int)(ld_relaxed(&S->f0[tid * 96]) - 32u * e) < 0 && ++guard < 200000);
            __syncwarp(0xff);
            if (tid == 0) *ep = e;
        }
        return;
    }
    const int role = pair * 2 + rank;
    const int gg = role >> 4, ii = role & 15;
    const int r = (gg >> 1) * 4 + (ii >> 2);
    const int j = (gg & 1) * 4 + (ii & 3);
    const int rh = 2 * r + (j & 1), c4 = j >> 1;
    const uint32_t bar0 = sb + OFF_BAR;
    unsigned* const f0 = &S->f0[j * 96];
#define BAR(i) (bar0 + 8 * (i))
#define CLUSTER_ARRIVE() asm volatile("barrier.cluster.arrive.relaxed.aligned;" ::: "memory")

    if (warp == 8) {
        if (lane == 0) {
#pragma unroll
            for (int q = 0; q < 16; q++) mbar_init(BAR(q), 1);
            asm volatile("fence.mbarrier_init.release.cluster;" ::: "memory");
        }
        __syncwarp();
        asm volatile("bar.arrive 4, 384;" ::: "memory");
        if (lane == 0) {
#define P1_ISSUE(kb) { \
                mbar_expect(BAR(B_X + kb), kb < 5 ? 32768 : 16384); \
                tma2d(sb + OFF_X + kb * 16384, &P.mx, kb * 64, r * 128, BAR(B_X + kb)); \
                if (kb < 5) { \
                    tma2d(sb + OFF_SLOT + kb * 16384, &P.mwqkv, 512 + 64 * j, kb * 64, BAR(B_X + kb)); \
                    tma2d(sb + OFF_SLOT + kb * 16384 + 8192, &P.mwqkv, 1024 + 64 * j, kb * 64, BAR(B_X + kb)); \
                } }
#pragma unroll 1
            for (int kb = 0; kb < PACE; kb++) P1_ISSUE(kb)
            mbar_expect(BAR(B_ST), 16384 + 3 * 4096 + 2048 + 256 + 16);
            bulk1d(sb + OFF_SX, p_x + (size_t)(128 * r + 16 * j) * 512, 16384, BAR(B_ST));
#pragma unroll 1
            for (int q = 0; q < 3; q++) tma2d(sb + OFF_SX + 16384 + q * 4096, &P.mw32, (q < 2 ? 512 + 512 * q : 0) + 64 * j, 32 * r, BAR(B_ST));
            bulk1d(sb + OFF_EP, &S->ep[role * 32], 16, BAR(B_ST));
            bulk1d(sb + OFF_SX + 28672, p_wphi + 1024 * j, 2048, BAR(B_ST));
            bulk1d(sb + OFF_SX + 30720, p_bsp + 128 * r, 256, BAR(B_ST));
            asm volatile("prefetch.tensormap [%0];" :: "l"(&P.mwo) : "memory");
            asm volatile("prefetch.tensormap [%0];" :: "l"(&P.mwsp) : "memory");
            asm volatile("prefetch.tensormap [%0];" :: "l"(&P.mwout) : "memory");
            asm volatile("prefetch.tensormap [%0];" :: "l"(&P.mout) : "memory");
        }
        __syncwarp();
    }
    if (warp > 8) {
        if (lane == 0) {
            const uint32_t b0 = BAR(warp == 9 ? 16 : warp == 10 ? 52 : 96);
#pragma unroll
            for (int q = 0; q < 44; q++) mbar_init(b0 + 8 * q, warp == 11 ? 2 : 1);
            if (warp == 9) { mbar_init(BAR(B_AUX1), 3); mbar_init(BAR(B_AUX2), 3); }
            asm volatile("fence.mbarrier_init.release.cluster;" ::: "memory");
        }
        __syncwarp();
    }
    if (warp >= 8) {
      asm volatile("setmaxnreg.dec.sync.aligned.u32 104;");
      if (warp == 8) {
        bar_sync(5, 288);
        CLUSTER_ARRIVE();
#pragma unroll 1
        for (int kb = PACE; kb < 12; kb++) {
            if (kb < 8) {
                mbar_wait(BAR(B_X + kb - PACE), 0);
                if (kb == 6) bar_sync(9, 256 + SBOTH * 128);
                if (lane == 0) P1_ISSUE(kb)
            }
            if (kb >= 5) {
                const int b = kb - 5;
                if (b < 6) mbar_wait(BAR(B_EW + b), 0);
                else bar_sync(8, 320);
                if (lane == 0) {
                    const uint32_t fb = BAR(B_W + 5 + b);
                    const uint32_t dst = sb + OFF_SLOT + (b < 5 ? b : 8 - b) * 16384;
                    mbar_expect(fb, 16384);
                    const int col = b < 3 ? 512 + 64 * j : 64 * j, row = b < 3 ? (5 + b) * 64 : (b - 3) * 128;
                    tma2d(dst, &P.mwqkv, col, row, fb);
                    tma2d(dst + 8192, &P.mwqkv, b < 3 ? col + 512 : col, b < 3 ? row : row + 64, fb);
                    if (b == 5) {
                        mbar_expect(BAR(B_WO), 131072);
                        tma2d(sb + OFF_X, &P.mwo, 128 * c4, 0, BAR(B_WO));
                    }
                }
            }
        }
        const unsigned epoch = *(const unsigned*)(sp + OFF_EP) + 1u;
#pragma unroll 1
        for (int q = 1; q < 4; q++) {
            mbar_wait(BAR(B_EQ + q), 0);
            if (lane == 0) tma2d(sb + OFF_X + q * 32768, &P.mwo, 128 * c4 + 64 * (q >> 1), (q & 1) * 256, BAR(B_WO));
        }
        if (lane == 0) { wait_flag(f0 + 64, 48u * epoch); fence_async_global(); }
        mbar_wait(BAR(B_KV), 0);
        const int kbl = (2 * c4 + lane) & 7;
#define SKIPLOCAL true
        POLL_ISSUE(8, &S->fo[rh * 32 + kbl],
                   mbar_expect(BAR(B_O + lane), 8192);
                   bulk1d(sb + OFF_O + lane * 8192, S->obuf + (rh * 64 + kbl * 8) * 256, 8192, BAR(B_O + lane)))
#pragma unroll 1
        for (int b = 0; b < 16; b++) {
            if (b == 8) {
                const int hf = lane & 1, pos = 2 + (lane >> 1), kbh = (2 * c4 + pos) & 7, sl = hf * 8 + pos;
#undef SKIPLOCAL
#define SKIPLOCAL false
                POLL_ISSUE(12, &S->fh[(2 * r + hf) * 32 + kbh],
                           mbar_expect(BAR(B_H + sl), 8192);
                           bulk1d(sb + OFF_X + sl * 8192, S->hbuf + ((2 * r + hf) * 64 + kbh * 8) * 256, 8192, BAR(B_H + sl)))
#undef SKIPLOCAL
#define SKIPLOCAL true
            }
            mbar_wait(b < 8 ? BAR(B_EO + ((0x77542100 >> (4 * b)) & 7)) : BAR(B_EI + b - 8), 0);
            if (lane == 0) {
                mbar_expect(BAR(B_WI + b), 11264);
                bulk1d(sb + OFF_W + (b & 7) * 11264, S->wpk + (j * 16 + (b & 8) + ((2 * c4 + b) & 7)) * 704, 11264, BAR(B_WI + b));
            }
        }
        {
            const int kl = P3_KB(15) & ~1;
            const unsigned* fl = lane < 30 ? &S->fz[P3_KB(lane >> 1) * 32 + 2 * c4 + (lane & 1)] : &S->fz[(kl + (lane & 1)) * 32 + j];
            bool mine = (int)(ld_acquire(fl) - epoch) >= 0;
            unsigned ready = 0;
            mbar_wait(BAR(B_ZH), 0);
#pragma unroll 1
            for (int it = 0; it < 17; it++) {
                const int s = it & 3, kb = it < 15 ? P3_KB(it) : kl + it - 15;
                if (it == 2) mbar_wait(BAR(B_DZ), 0);
                if (it >= 4) mbar_wait(BAR(B_E + s), ((it >> 2) - 1) & 1);
                if (lane == 0) {
                    mbar_expect(BAR(B_F + s), it < 15 ? 16384 + 22528 : 16384 + 11264);
                    tma2d(sb + P3_A(s), &P.mwsp, kb * 64, r * 128, BAR(B_F + s));
                }
                if (it == 0) {
                    mbar_wait_cluster(BAR(B_LZ), 0);
                    fence_async_global();
                } else if (it < 16 && ((ready >> (2 * it)) & 3u) != 3u) {
                    do {
                        if (!mine) mine = (int)(ld_acquire(fl) - epoch) >= 0;
                        ready = __ballot_sync(0xffffffffu, mine);
                    } while (((ready >> (2 * it)) & 3u) != 3u);
                    __syncwarp();
                    fence_async_global();
                }
                if (lane == 0) {
                    const uint32_t* src = S->zbuf + (kb * 88 + c4 * 22) * 256;
                    const uint32_t dst = sb + P3_B(s);
                    bulk1d(dst, src + rank * 2816, 11264, BAR(B_F + s));
                    if (it < 15) bulk1d(dst + 11264, src + (rank ^ 1) * 2816, 11264, BAR(B_F + s));
                }
            }
        }
#pragma unroll 1
        for (int b = 0; b < 12; b++) {
            if (b == 7) {
                bar_sync(11, 352);
                POLL_ISSUE(8, &S->fu[rh * 32 + kbl],
                           mbar_expect(BAR(B_U + lane), 11264);
                           bulk1d(sb + OFF_U + lane * 11264, S->ubuf + (rh * 88 + kbl * 11) * 256, 11264, BAR(B_U + lane)))
            }
            if (b < 7) mbar_wait(BAR(B_E + ((0x0332221 >> (4 * b)) & 3)), b < 6);
            if (b >= 7) mbar_wait(BAR(B_ET + b - 7), 0);
            if (lane == 0) {
                const uint32_t dst = sb + P3_WT(b);
                const int q = (b * 11) >> 5, row = ((c4 + q) & 3) * 176 + (b - 3 * q) * 64;
                mbar_expect(BAR(B_WT + b), 16384);
                tma2d(dst, &P.mwout, 128 * c4, row, BAR(B_WT + b));
                tma2d(dst + 8192, &P.mwout, 128 * c4 + 64, row, BAR(B_WT + b));
            }
        }
      } else {
        const int c = lane & 3;
        bar_sync(4, 384);
        CLUSTER_ARRIVE();
        if (warp == 10 && r == 0) {
            float4* z = (float4*)&S->kv[j * 4 * KV_HEAD];
#pragma unroll 1
            for (int q = lane; q < KV_HEAD; q += 32) z[q] = make_float4(0, 0, 0, 0);
            __syncwarp();
            asm volatile("fence.acq_rel.gpu;" ::: "memory");
        }
        mbar_wait(BAR(B_ST), 0);
        const unsigned epoch = *(const unsigned*)(sp + OFF_EP) + 1u;
        if (warp == 10 && r == 0 && lane == 0) st_relaxed(f0 + 1, epoch);
        if (warp < 11) {
#pragma unroll 1
            for (int i = (warp - 9) * 8; i < (warp - 9) * 8 + 8; i++) {
                const unsigned short* q = (const unsigned short*)(sp + OFF_SX + 28672) + 2 * c * 16 + (lane >> 2) + (i >> 2) * 256 + (i & 1) * 128 + ((i >> 1) & 1) * 8;
                *(uint32_t*)(sp + OFF_WB + (i >> 2) * 512 + lane * 16 + (i & 3) * 4) = (uint32_t)q[0] | ((uint32_t)q[16] << 16);
            }
            const uint32_t bv = *(const uint32_t*)(sp + OFF_SX + 30720 + (warp - 9) * 128 + lane * 4);
            *(float2*)(sp + OFF_BSP + (warp - 9) * 256 + lane * 8) = make_float2(lo_f(bv), hi_f(bv));
        }
        __syncwarp();
        asm volatile("bar.arrive 9, %0;" :: "n"(256 + SBOTH * 128) : "memory");
        bar_sync(10, 224 + SBOTH * 128);
        __nanosleep(GSLEEP);
#pragma unroll 1
        for (int st = 0; st < 2; st++) {
            if (warp == 9) {
                if (st == 0) {
                    uint4 w[2];
                    while (true) {
                        w[0] = ld_relaxed4(&S->st1[128 * r + 2 * lane]); w[1] = ld_relaxed4(&S->st1[128 * r + 64 + 2 * lane]);
                        const unsigned bad = (w[0].x ^ epoch) | (w[0].y ^ epoch) | (w[0].z ^ epoch) | (w[0].w ^ epoch) | (w[1].x ^ epoch) | (w[1].y ^ epoch) | (w[1].z ^ epoch) | (w[1].w ^ epoch);
                        if (__all_sync(0xffffffffu, (bad & 3u) == 0)) break;
                    }
#pragma unroll
                    for (int q = 0; q < 2; q++) {
                        const float m0 = __uint_as_float(w[q].x) * (1.f / 512.f), m1 = __uint_as_float(w[q].z) * (1.f / 512.f);
                        const float r0 = rsq(fmaxf(__uint_as_float(w[q].y) * (1.f / 512.f) - m0 * m0, 0.f) + 1e-5f);
                        const float r1 = rsq(fmaxf(__uint_as_float(w[q].w) * (1.f / 512.f) - m1 * m1, 0.f) + 1e-5f);
                        asm volatile("st.shared.v4.f32 [%0], {%1,%2,%3,%4};" :: "r"(sb + OFF_ST1 + q * 512 + lane * 16), "f"(-m0 * r0), "f"(r0), "f"(-m1 * r1), "f"(r1) : "memory");
                    }
                    if (lane == 0) wait_flag(f0 + 1, epoch);
                } else {
                  bar_sync(8, 320);
                  if (lane == 0) {
                    red_release(f0, 2);
                    wait_flag(f0, 32u * epoch);
                    XSTAMP(8);
                    fence_async_global();
                    mbar_expect(BAR(B_KV), 4 * KV_HEAD * 4);
                    bulk1d(sb + OFF_KVS, &S->kv[j * 4 * KV_HEAD], 4 * KV_HEAD * 4, BAR(B_KV));
                  }
                }
            } else {
                const int col4 = (warp - 10) * 24 + (lane < 24 ? lane : 0) + st * 48;
                const float4* p = (const float4*)&S->cs[j * 16 * 384] + col4;
                int guard = 0;
                if (st == 1) { if (lane == 0) { while ((int)(ld_relaxed(f0 + 64) - 48u * epoch) < 0 && ++guard < 400000) __nanosleep(500); } __syncwarp(); }
                while (true) {
                    if (++guard > 400000) __trap();
                    float4 acc = make_float4(0, 0, 0, 0); unsigned bad = 0;
#pragma unroll
                    for (int q = 0; q < 16; q++) {
                        const uint4 v = ld_relaxed4(p + q * 96);
                        bad |= (v.x ^ epoch) | (v.y ^ epoch) | (v.z ^ epoch) | (v.w ^ epoch);
                        acc.x += __uint_as_float(v.x); acc.y += __uint_as_float(v.y); acc.z += __uint_as_float(v.z); acc.w += __uint_as_float(v.w);
                    }
                    asm volatile("st.shared.v4.f32 [%0], {%1,%2,%3,%4};" :: "r"(sb + OFF_CS + col4 * 16), "f"(acc.x), "f"(acc.y), "f"(acc.z), "f"(acc.w) : "memory");
                    if (__all_sync(0xffffffffu, (bad & 3u) == 0)) break;
                }
            }
            __syncwarp();
            if (st == 1) break;
            if (lane == 0) mbar_arrive(BAR(B_AUX1));
            XSTAMP(warp - 4);
            uint4 cw[8];
            const int r8 = lane & 7;
#pragma unroll
            for (int h = 0; h < 2; h++) {
                const int chunk = (warp - 9) * 8 + h * 4 + (lane >> 3), part = chunk >= 11, cc = chunk - 11 * part;
                const bool cvalid = chunk < 22 && (88 * j + cc * 8 < 688);
                const bf16* ptr = p_win + (cvalid ? (part ? 0 : 688) + 88 * j + cc * 8 : 0) + (size_t)(32 * r + r8) * 1376;
#pragma unroll
                for (int q = 0; q < 4; q++) cw[4 * h + q] = cvalid ? __ldg((const uint4*)(ptr + q * 8 * 1376)) : make_uint4(0, 0, 0, 0);
            }
            {
#pragma unroll
                for (int h = 0; h < 2; h++) {
                    const int chunk = (warp - 9) * 8 + h * 4 + (lane >> 3), part = chunk >= 11, cc = chunk - 11 * part;
                    if (chunk < 22) {
                        uint4* dst = S->wpk + ((j * 2 + part) * 8 + (r >> 1)) * 704 + cc * 64 + (r & 1) * 32 + r8;
#pragma unroll
                        for (int q = 0; q < 4; q++) dst[q * 8] = cw[4 * h + q];
                    }
                    st_relaxed((uint32_t*)&S->cs[(j * 16 + r) * 384 + 192 + chunk * 8 + r8], tagf(colsum8(&cw[4 * h], lane), epoch));
                }
            }
            __syncwarp();
            if (lane == 0) red_release(f0 + 64, 1);
        }
        if (warp == 11) {
            if (lane == 0) {
                mbar_arrive(BAR(B_AUX2));
                l2_prefetch((const char*)p_wout + role * 5504, 5504);
            }
            mbar_wait_watchdog(BAR(B_END));
            if (lane == 0) S->ep[role * 32] = epoch;
        } else {
            const int half = warp - 9;
            mbar_wait(BAR(B_KV), 0);
            mbar_wait_cluster(BAR(B_LO + half), 0);
            if (lane == 0) {
                fence_async_global();
                mbar_expect(BAR(B_O + half), 8192);
                bulk1d(sb + OFF_O + half * 8192, S->obuf + (rh * 64 + (2 * c4 + half) * 8) * 256, 8192, BAR(B_O + half));
            }
            mbar_wait(BAR(B_EO + 7), 0);
#pragma unroll 1
            for (int p = 0; p < 2; p++) {
                mbar_wait_cluster(BAR(B_LH + half * 2 + p), 0);
                if (lane == 0) {
                    fence_async_global();
                    mbar_expect(BAR(B_H + half * 8 + p), 8192);
                    bulk1d(sb + OFF_X + (half * 8 + p) * 8192, S->hbuf + ((2 * r + half) * 64 + (2 * c4 + p) * 8) * 256, 8192, BAR(B_H + half * 8 + p));
                }
            }
#pragma unroll 1
            for (int q = 0; q < 8; q++) mbar_wait(BAR(B_H + half * 8 + q), 0);
#pragma unroll
            for (int q = 0; q < 2; q++) {
                const int row = half * 64 + q * 32 + lane;
                const float4* p = (const float4*)&S->st2[(128 * r + row) * 8];
                const float4 a = __ldcg(p), b = __ldcg(p + 1), cc = __ldcg(p + 2), d = __ldcg(p + 3);
                const float mu = ((a.x + a.z) + (b.x + b.z) + (cc.x + cc.z) + (d.x + d.z)) * (1.f / 512.f);
                const float m2 = ((a.y + a.w) + (b.y + b.w) + (cc.y + cc.w) + (d.y + d.w)) * (1.f / 512.f);
                const float rs = 0.5f * rsq(fmaxf(m2 - mu * mu, 0.f) + 1e-5f);
                sts_f2(sb + OFF_ST2 + row * 8, -mu * rs, rs);
            }
            __syncwarp();
            if (lane == 0) mbar_arrive(BAR(B_AUX2));
            bar_sync(6 + half, 160);
            if (lane == 0) { st_release(&S->fz[(2 * r + half) * 32 + j], epoch); mbar_arrive_cluster(BAR(B_LZ), half); }
            __syncwarp();
            bar_sync(11, 352);
            mbar_wait_cluster(BAR(B_LU + half), 0);
            if (lane == 0) {
                fence_async_global();
                mbar_expect(BAR(B_U + half), 11264);
                bulk1d(sb + OFF_U + half * 11264, S->ubuf + (rh * 88 + (2 * c4 + half) * 11) * 256, 11264, BAR(B_U + half));
            }
        }
      }
    } else {
        const int wg = warp >> 2, w4 = warp & 3, g = lane >> 2, c = lane & 3;
        const bool elect = (tid & 127) == 0;
        const uint32_t rowoff = wg * 64 + w4 * 16 + g;
        const uint32_t imgoff = 2 * w4 * 32 + lane;
        bar_sync(4, 384);
        asm volatile("bar.arrive 5, 288;" ::: "memory");
        CLUSTER_ARRIVE();
        uint32_t* const st3_own = (uint32_t*)&S->st3[j * 1024 + (2 * r + wg) * 32 + w4 * 8] + lane;
        *st3_own = 0u;
        unsigned epoch;
        uint32_t phq[32];
        float qinv[16];
        {
            float akv[64], aq[32];
            const uint64_t dxa = mkdesc(sb + OFF_X + wg * 8192, 16, 1024, 1);
            const uint64_t dsl = mkdesc(sb + OFF_SLOT, 8192, 1024, 1);
#pragma unroll 1
            for (int kb = 0; kb < 8; kb++) {
                mbar_wait(BAR(B_X + kb), 0);
                if (kb >= 5) mbar_wait(BAR(B_W + kb), 0);
                if (kb == 0) STAMP(0);
                const uint64_t da = dxa + kb * 1024, db = dsl + (kb < 5 ? kb : kb - 5) * 1024;
                wg_fence();
#pragma unroll
                for (int ks = 0; ks < 4; ks++) wgmma_n128_t01(akv, da + ks * 2, db + ks * 128, (kb | ks) != 0);
                wg_commit();
                wg_wait<1>();
                if (elect && kb >= 1 && kb <= 5) mbar_arrive(BAR(B_EW + kb - 1));
                if (kb == SKB && (wg == 0 || SBOTH)) {
                    mbar_wait(BAR(B_ST), 0);
                    const unsigned ep = *(const unsigned*)(sp + OFF_EP) + 1u;
#pragma unroll 1
                    for (int vt = tid; vt < 256; vt += (SBOTH ? 256 : 128)) {
                        const int vw = vt >> 5;
                        uint4 cw[4];
                        const uint32_t o = OFF_SX + 16384 + (vw < 6 ? (vw >> 1) * 4096 : 0) + (lane & 7) * 128 + ((((vw & 1) * 4 + (lane >> 3)) ^ (lane & 7)) * 16);
#pragma unroll
                        for (int q = 0; q < 4; q++) cw[q] = *(const uint4*)(sp + o + q * 1024);
                        float r1 = 0, r2 = 0;
#pragma unroll
                        for (int q = 0; q < 4; q++) {
                            const uint4 v = *(const uint4*)(sp + OFF_SX + (vt >> 4) * 1024 + (vt & 15) * 16 + q * 256);
                            const uint32_t w[4] = {v.x, v.y, v.z, v.w};
                            float t1 = 0, t2 = 0;
#pragma unroll
                            for (int e = 0; e < 4; e++) { float lo = lo_f(w[e]), hi = hi_f(w[e]); t1 += lo + hi; t2 = fmaf(lo, lo, t2); t2 = fmaf(hi, hi, t2); }
                            r1 += t1; r2 += t2;
                        }
                        const float csum = colsum8(cw, lane);
                        { const bool up = lane & 1; float t = __shfl_xor_sync(0xffffffffu, up ? r1 : r2, 1); r1 = (up ? r2 : r1) + t; }
#pragma unroll
                        for (int o2 = 2; o2 < 16; o2 <<= 1) r1 += __shfl_xor_sync(0xffffffffu, r1, o2);
                        if ((lane & 15) < 2) st_relaxed((uint32_t*)&S->st1[128 * r + 16 * j + (vt >> 4)] + (lane & 1), tagf(r1, ep));
                        if (vt < 192) st_relaxed((uint32_t*)&S->cs[(j * 16 + r) * 384 + vt], tagf(csum, ep));
                    }
                    asm volatile("bar.arrive 9, %0;" :: "n"(256 + SBOTH * 128) : "memory");
                    asm volatile("bar.arrive 10, %0;" :: "n"(224 + SBOTH * 128) : "memory");
                    if (warp == 0) XSTAMP(9);
                }
            }
            STAMP(1);
#define Q_PART(q0, q1) _Pragma("unroll 1") for (int q = (q0); q < (q1); q++) { \
                    mbar_wait(BAR(B_Q + q), 0); \
                    const uint64_t da = dxa + q * 2048, db = dsl + (q < 2 ? 3 + q : 5 - q) * 1024; \
                    wg_fence(); \
                    _Pragma("unroll") for (int ks = 0; ks < 8; ks++) wgmma_n64_t01(aq, da + (ks >> 2) * 1024 + (ks & 3) * 2, db + ks * 128, (q | ks) != 0); \
                    wg_commit(); \
                    wg_wait<1>(); \
                    if (elect && q >= 2) mbar_arrive(BAR(B_EQ + q - 1)); }
            Q_PART(0, 1)
            wg_wait<0>();
            pin(akv); pin(aq);
            if (elect) mbar_arrive(BAR(B_EQ));
            asm volatile("setmaxnreg.inc.sync.aligned.u32 200;");
            if (warp == 0) XSTAMP(0);
            mbar_wait(BAR(B_AUX1), 0);
            if (warp == 0) XSTAMP(2);
            epoch = *(const unsigned*)(sp + OFF_EP) + 1u;
            const float2 s0 = SF2(OFF_ST1 + rowoff * 8), s1 = SF2(OFF_ST1 + (rowoff + 8) * 8);
#define FOLD(dst, i0, csb) _Pragma("unroll") for (int t = 0; t < 2; t++) { \
                    const float2 cs = SF2((csb) + t * 32); \
                    dst[2 * t] = pack2(fmaf(akv[(i0) + 4 * t], s0.y, s0.x * cs.x), fmaf(akv[(i0) + 4 * t + 1], s0.y, s0.x * cs.y)); \
                    dst[2 * t + 1] = pack2(fmaf(akv[(i0) + 4 * t + 2], s1.y, s1.x * cs.x), fmaf(akv[(i0) + 4 * t + 3], s1.y, s1.x * cs.y)); }
#define PROJECT(csoff) _Pragma("unroll") for (int hh = 0; hh < 4; hh++) { \
                    uint32_t a[4]; const uint4 wb = *(const uint4*)(sp + OFF_WB + hh * 512 + lane * 16); \
                    FOLD(a, 8 * hh, OFF_CS + c * 8 + (csoff) + 64 * hh) \
                    mma16816z(&pp[8 * hh], a, wb.x, wb.y); mma16816z(&pp[8 * hh + 4], a, wb.z, wb.w); }
            float pp[32];
            {
                PROJECT(0)
                uint32_t vv[16];
#pragma unroll
                for (int hh = 0; hh < 4; hh++) { uint32_t* a = &vv[4 * hh]; FOLD(a, 32 + 8 * hh, OFF_CS + c * 8 + 256 + 64 * hh) }
                feature_map4<true>(pp, phq);
                if (warp == 0) XSTAMP(3);
                bar_sync(1, 256);
                const uint32_t stoff = ((lane >> 4) & 1) * 2048 + (8 * wg + 2 * w4 + ((lane >> 3) & 1)) * 128 + (lane & 7) * 16;
#pragma unroll
                for (int hh = 0; hh < 4; hh++) stsm4(sb + OFF_VST + (hh >> 1) * 10240 + (hh & 1) * 4096 + stoff, vv[4 * hh], vv[4 * hh + 1], vv[4 * hh + 2], vv[4 * hh + 3]);
                asm volatile("st.shared.v4.u32 [%0], {%1,%1,%1,%1};" :: "r"(sb + OFF_VST + wg * 10240 + 8192 + (tid & 127) * 16), "r"(0x3f803f80u) : "memory");
#pragma unroll
                for (int i = 0; i < 8; i++) stsm4(sb + OFF_PHI + i * 4096 + stoff, phq[4 * i], phq[4 * i + 1], phq[4 * i + 2], phq[4 * i + 3]);
                fence_async_smem();
                bar_sync(1, 256);
                float kvp[32];
                const uint64_t da = mkdesc(sb + OFF_VST + wg * 10240, 128, 2048, 0), db = mkdesc(sb + OFF_PHI + wg * 16384, 128, 2048, 0);
                wg_fence();
#pragma unroll
                for (int ks = 0; ks < 8; ks++) wgmma_n64_t11(kvp, da + ks * 16, db + ks * 16, ks != 0);
                wg_commit();
                wg_wait<0>();
                pin(kvp);
                if (warp == 0) XSTAMP(4);
                float* dst = &S->kv[(4 * j + 2 * wg) * KV_HEAD + lane * 4];
                if (w4 == 0) {
#pragma unroll
                    for (int t = 0; t < 4; t++) red_f32x4(dst + t * 128, kvp[4 * t], kvp[4 * t + 1], kvp[4 * t + 2], kvp[4 * t + 3]);
                } else if (w4 == 1) {
#pragma unroll
                    for (int t = 0; t < 4; t++) red_f32x4(dst + KV_HEAD + t * 128, kvp[16 + 4 * t], kvp[17 + 4 * t], kvp[18 + 4 * t], kvp[19 + 4 * t]);
                } else if (w4 == 2 && lane < 4) {
#pragma unroll
                    for (int t = 0; t < 4; t++)
                        red_f32x4(dst + (t >> 1) * KV_HEAD + 512 + (t & 1) * 16, kvp[8 * t], kvp[8 * t + 1], kvp[8 * t + 4], kvp[8 * t + 5]);
                }
                asm volatile("bar.arrive 8, 320;" ::: "memory");
                STAMP(2);
                Q_PART(1, 4)
                wg_wait<0>();
                pin(aq);
                if (elect) mbar_arrive(BAR(B_EQ + 3));
#pragma unroll
                for (int i = 0; i < 32; i++) akv[i] = aq[i];
                PROJECT(512)
                feature_map4<false>(pp, phq);
#pragma unroll
                for (int i = 0; i < 8; i++) {
                    float t[4];
                    mma16816z(t, &phq[4 * i], 0x3f803f80u, 0x3f803f80u);
                    qinv[2 * i] = rcp(t[0]); qinv[2 * i + 1] = rcp(t[2]);
                }
            }
        }
        uint32_t hres[16];
        const size_t tile_off = (size_t)(64 * rh + 16 * w4 + g) * 256 + 64 * c4 + 32 * wg + c;
        STAMP(3);
        {
            asm volatile("barrier.cluster.wait.acquire.aligned;" ::: "memory");
            mbar_wait(BAR(B_KV), 0);
            STAMP(4);
            uint32_t* dst = S->obuf + ((2 * r + wg) * 64 + 8 * j) * 256 + imgoff;
#pragma unroll
            for (int hh = 0; hh < 4; hh++) {
                float n0[2][4], n1[2][4], dn[2][4];
#pragma unroll
                for (int ks = 0; ks < 2; ks++) {
                    const uint32_t* a = &phq[hh * 8 + ks * 4];
                    const float4 u = *(const float4*)(sp + OFF_KVS + (hh * KV_HEAD + (2 * ks) * 128) * 4 + lane * 16);
                    const float4 v = *(const float4*)(sp + OFF_KVS + (hh * KV_HEAD + (2 * ks + 1) * 128) * 4 + lane * 16);
                    const float4 z = *(const float4*)(sp + OFF_KVS + (hh * KV_HEAD + 512 + ks * 16) * 4 + c * 16);
                    mma16816z(n0[ks], a, pack2(u.x, u.y), pack2(v.x, v.y));
                    mma16816z(n1[ks], a, pack2(u.z, u.w), pack2(v.z, v.w));
                    mma16816z(dn[ks], a, pack2(z.x, z.y), pack2(z.z, z.w));
                }
                const float* qi = &qinv[4 * hh];
                const float r0 = rcp(fmaf(dn[0][0], qi[0], fmaf(dn[1][0], qi[2], 1e-6f))), r1 = rcp(fmaf(dn[0][2], qi[1], fmaf(dn[1][2], qi[3], 1e-6f)));
                const float p0 = qi[0] * r0, m0 = qi[2] * r0, p1 = qi[1] * r1, m1 = qi[3] * r1;
                dst[(2 * hh) * 256] = pack2(fmaf(n0[0][0], p0, n0[1][0] * m0), fmaf(n0[0][1], p0, n0[1][1] * m0));
                dst[(2 * hh) * 256 + 32] = pack2(fmaf(n0[0][2], p1, n0[1][2] * m1), fmaf(n0[0][3], p1, n0[1][3] * m1));
                dst[(2 * hh + 1) * 256] = pack2(fmaf(n1[0][0], p0, n1[1][0] * m0), fmaf(n1[0][1], p0, n1[1][1] * m0));
                dst[(2 * hh + 1) * 256 + 32] = pack2(fmaf(n1[0][2], p1, n1[1][2] * m1), fmaf(n1[0][3], p1, n1[1][3] * m1));
            }
            bar_sync(2 + wg, 128);
            if (elect) { st_release(&S->fo[(2 * r + wg) * 32 + j], epoch); mbar_arrive_cluster(BAR(B_LO + rank), wg); }
            STAMP(5);
        }
        {
            const uint32_t* xp = (const uint32_t*)p_x + tile_off;
#pragma unroll
            for (int i = 0; i < 8; i++) { hres[2 * i] = __ldg(xp + 4 * i); hres[2 * i + 1] = __ldg(xp + 4 * i + 8 * 256); }
        }
        {
            float acc[32];
            mbar_wait(BAR(B_WO), 0);
            const uint64_t da = mkdesc(sb + OFF_O, 1024, 128, 0), db0 = mkdesc(sb + OFF_X + wg * 65536, 8192, 1024, 1);
#pragma unroll 1
            for (int kb = 0; kb < 8; kb++) {
                mbar_wait(BAR(B_O + kb), 0);
                const uint64_t db = db0 + ((2 * c4 + kb) & 7) * 512;
                if (kb == 0) STAMP(6);
                wg_fence();
#pragma unroll
                for (int ks = 0; ks < 4; ks++) wgmma_n64_t01(acc, da + (kb * 4 + ks) * 128, db + ks * 128, (kb | ks) != 0);
                wg_commit();
                wg_wait<1>();
                if (elect && kb >= 1) mbar_arrive(BAR(B_EO + kb - 1));
            }
            wg_wait<0>();
            pin(acc);
            if (elect) mbar_arrive(BAR(B_EO + 7));
            STAMP(7);
            const int ct = 2 * c4 + wg;
            uint32_t* dst = S->hbuf + (rh * 64 + 8 * ct) * 256 + imgoff;
            float sa = 0, sbb = 0, qa = 0, qb = 0;
#pragma unroll
            for (int i = 0; i < 8; i++) {
                const float h0 = lo_f(hres[2 * i]) + acc[4 * i], h1 = hi_f(hres[2 * i]) + acc[4 * i + 1];
                const float h2 = lo_f(hres[2 * i + 1]) + acc[4 * i + 2], h3 = hi_f(hres[2 * i + 1]) + acc[4 * i + 3];
                hres[2 * i] = pack2(h0, h1); hres[2 * i + 1] = pack2(h2, h3);
                dst[i * 256] = hres[2 * i]; dst[i * 256 + 32] = hres[2 * i + 1];
                sa += h0 + h1; qa = fmaf(h0, h0, qa); qa = fmaf(h1, h1, qa);
                sbb += h2 + h3; qb = fmaf(h2, h2, qb); qb = fmaf(h3, h3, qb);
            }
            ((float*)S->st2)[((64 * rh + 16 * w4 + g + 8 * (c >> 1)) * 8 + ct) * 2 + (c & 1)] = quad_reduce4(sa, qa, sbb, qb, c);
            bar_sync(2 + wg, 128);
            if (elect) { st_release(&S->fh[rh * 32 + ct], epoch); mbar_arrive_cluster(BAR(B_LH + rank * 2 + wg), 0); mbar_arrive_cluster(BAR(B_LH + rank * 2 + wg), 1); }
            STAMP(8);
        }
        float az1[44];
#define GELU44(A, csoff, i0, i1) { \
            const float2 s0 = SF2(OFF_ST2 + rowoff * 8), s1 = SF2(OFF_ST2 + (rowoff + 8) * 8);     \
            _Pragma("unroll") for (int i = (i0); i < (i1); i++) { \
                const float2 cs = SF2(OFF_CS + (csoff) * 4 + c * 8 + i * 32); \
                A[4 * i] = gelu_half(fmaf(A[4 * i], s0.y, s0.x * cs.x)); A[4 * i + 1] = gelu_half(fmaf(A[4 * i + 1], s0.y, s0.x * cs.y)); \
                A[4 * i + 2] = gelu_half(fmaf(A[4 * i + 2], s1.y, s1.x * cs.x)); A[4 * i + 3] = gelu_half(fmaf(A[4 * i + 3], s1.y, s1.x * cs.y)); \
            } }
        {
            float az2[44];
            const uint64_t da = mkdesc(sb + OFF_X + wg * 65536, 1024, 128, 0);
            const uint64_t dw = mkdesc(sb + OFF_W, 128, 1024, 0);
#pragma unroll 1
            for (int kb = 0; kb < 8; kb++) {
                mbar_wait(BAR(B_WI + kb), 0);
                mbar_wait(BAR(B_H + wg * 8 + kb), 0);
                if (kb == 0) STAMP(9);
                const uint64_t db = dw + kb * 704;
                wg_fence();
#pragma unroll
                for (int ks = 0; ks < 4; ks++) wgmma_n88_t01(az2, da + (kb * 4 + ks) * 128, db + ks * 16, (kb | ks) != 0);
                wg_commit();
                wg_wait<1>();
                if (elect && kb >= 1) mbar_arrive(BAR(B_EI + kb - 1));
            }
            mbar_wait(BAR(B_AUX2), 0);
            wg_wait<0>();
            pin(az2);
            if (elect) mbar_arrive(BAR(B_EI + 7));
            STAMP(10);
            GELU44(az2, 192, 0, 11)
            {
                float sa = 0, sbb = 0, qa = 0, qb = 0;
#pragma unroll
                for (int i = 0; i < 11; i++) {
                    sa += az2[4 * i] + az2[4 * i + 1]; qa = fmaf(az2[4 * i], az2[4 * i], qa); qa = fmaf(az2[4 * i + 1], az2[4 * i + 1], qa);
                    sbb += az2[4 * i + 2] + az2[4 * i + 3]; qb = fmaf(az2[4 * i + 2], az2[4 * i + 2], qb); qb = fmaf(az2[4 * i + 3], az2[4 * i + 3], qb);
                }
                st_relaxed(st3_own, __float_as_uint(quad_reduce4(sa, qa, sbb, qb, c)) | 1u);
                STAMP(11);
            }
#pragma unroll 1
            for (int pass = 0; pass < 2; pass++) {
#pragma unroll 1
                for (int kb = (pass == 0 ? 0 : ZSPLIT); kb < (pass == 0 ? ZSPLIT : 8); kb++) {
                    mbar_wait(BAR(B_WI + 8 + kb), 0);
                    const uint64_t db = dw + kb * 704;
                    wg_fence();
#pragma unroll
                    for (int ks = 0; ks < 4; ks++) wgmma_n88_t01(az1, da + (kb * 4 + ks) * 128, db + ks * 16, (kb | ks) != 0);
                    wg_commit();
                    wg_wait<1>();
                    if (elect && kb == 4) mbar_arrive(BAR(B_ZH));
                }
                wg_wait<0>();
                pin(az1);
                if (pass == 1) break;
                uint4 w[2];
                const uint4* p3 = &S->st3[(2 * c) * 1024 + (2 * r + wg) * 32 + w4 * 8 + g];
                while (true) {
                    w[0] = ld_relaxed4(p3); w[1] = ld_relaxed4(p3 + 1024);
                    const unsigned ok = w[0].x & w[0].y & w[0].z & w[0].w & w[1].x & w[1].y & w[1].z & w[1].w;
                    if (__all_sync(0xffffffffu, ok & 1u)) break;
                }
                const float m0 = quad_sum(__uint_as_float(w[0].x) + __uint_as_float(w[1].x)) * (1.f / 688.f);
                const float q0 = quad_sum(__uint_as_float(w[0].y) + __uint_as_float(w[1].y)) * (1.f / 688.f);
                const float m1 = quad_sum(__uint_as_float(w[0].z) + __uint_as_float(w[1].z)) * (1.f / 688.f);
                const float q1 = quad_sum(__uint_as_float(w[0].w) + __uint_as_float(w[1].w)) * (1.f / 688.f);
                const float rs0 = rsq(fmaxf(q0 - m0 * m0, 0.f) + 1e-5f), rs1 = rsq(fmaxf(q1 - m1 * m1, 0.f) + 1e-5f);
                const float mu0 = -m0 * rs0, mu1 = -m1 * rs1;
                STAMP(12);
                uint32_t* dst = S->zbuf + ((2 * r + wg) * 88 + 11 * j) * 256 + imgoff;
#pragma unroll
                for (int i = 0; i < 11; i++) {
                    dst[i * 256] = pack2(fmaf(az2[4 * i], rs0, mu0), fmaf(az2[4 * i + 1], rs0, mu0));
                    dst[i * 256 + 32] = pack2(fmaf(az2[4 * i + 2], rs1, mu1), fmaf(az2[4 * i + 3], rs1, mu1));
                }
                asm volatile("bar.arrive %0, 160;" :: "r"(6 + wg) : "memory");
                STAMP(13);
            }
            if (elect) { mbar_arrive(BAR(B_DZ)); mbar_arrive_cluster(BAR(B_PR), rank ^ 1); }
            GELU44(az1, 280, 0, 11)
            pin(az1);
            STAMP(14);
        }
        {
            float acc[44], acx[44];
            if (tid == 0) mbar_expect(BAR(B_XC), 22528);
            const uint64_t da0 = mkdesc(sb + wg * 8192, 16, 1024, 1), db0 = mkdesc(sb, 128, 1024, 0);
#pragma unroll 1
            for (int it = 0; it < 15; it++) {
                const int s = it & 3;
                mbar_wait(BAR(B_F + s), (it >> 2) & 1);
                if (it == 0) STAMP(15);
                const uint64_t da = da0 + (P3_A(s) >> 4), db = db0 + (P3_B(s) >> 4);
                wg_fence();
#pragma unroll
                for (int ks = 0; ks < 4; ks++) wgmma_n176_t01(acc, acx, da + ks * 2, db + ks * 16, (it | ks) != 0);
                wg_commit();
                wg_wait<1>();
                if (elect && it >= 1) mbar_arrive(BAR(B_E + ((it - 1) & 3)));
            }
            mbar_wait_cluster(BAR(B_PR), 0);
            uint32_t rdst, rbar;
            asm volatile("mapa.shared::cluster.u32 %0, %1, %2;" : "=r"(rdst) : "r"(sb + OFF_XC + tid * 16), "r"(rank ^ 1));
            asm volatile("mapa.shared::cluster.u32 %0, %1, %2;" : "=r"(rbar) : "r"(BAR(B_XC)), "r"(rank ^ 1));
            const float b0 = *(const float*)(sp + OFF_BSP + rowoff * 4), b1 = *(const float*)(sp + OFF_BSP + (rowoff + 8) * 4);
            wg_wait<0>();
            pin(acc); pin(acx);
            if (elect) mbar_arrive(BAR(B_E + 2));
#define PK(i) pack2(acx[2 * (i)], acx[2 * (i) + 1])
#pragma unroll
            for (int i = 0; i < 5; i++)
                asm volatile("st.async.weak.shared::cluster.mbarrier::complete_tx::bytes.v4.b32 [%0], {%1,%2,%3,%4}, [%5];"
                             :: "r"(rdst + i * 4096), "r"(PK(4 * i)), "r"(PK(4 * i + 1)), "r"(PK(4 * i + 2)), "r"(PK(4 * i + 3)), "r"(rbar) : "memory");
            asm volatile("st.async.weak.shared::cluster.mbarrier::complete_tx::bytes.v2.b32 [%0], {%1,%2}, [%3];"
                         :: "r"(rdst + 5 * 4096 - tid * 8), "r"(PK(20)), "r"(PK(21)), "r"(rbar) : "memory");
#pragma unroll
            for (int it = 15; it < 17; it++) {
                const int s = it & 3;
                mbar_wait(BAR(B_F + s), (it >> 2) & 1);
                const uint64_t da = da0 + (P3_A(s) >> 4), db = db0 + (P3_B(s) >> 4);
                wg_fence();
#pragma unroll
                for (int ks = 0; ks < 4; ks++) wgmma_n88_t01(acc, da + ks * 2, db + ks * 16, 1);
                wg_commit();
            }
            wg_wait<1>();
            if (elect) mbar_arrive(BAR(B_E + 3));
            wg_wait<0>();
            pin(acc);
            if (elect) mbar_arrive(BAR(B_E + 0));
            STAMP(16);
#pragma unroll
            for (int k = 0; k < 44; k++) acc[k] = (acc[k] + ((k & 2) ? b1 : b0)) * az1[k];
            mbar_wait_cluster(BAR(B_XC), 0);
            STAMP(17);
            uint32_t* dst = S->ubuf + ((2 * r + wg) * 88 + 11 * j) * 256 + imgoff;
            uint4 xo[6];
#pragma unroll
            for (int i = 0; i < 5; i++) xo[i] = *(const uint4*)(sp + OFF_XC + tid * 16 + i * 4096);
            { const uint2 t = *(const uint2*)(sp + OFF_XC + 5 * 4096 + tid * 8); xo[5] = make_uint4(t.x, t.y, 0, 0); }
            asm volatile("bar.arrive 11, 352;" ::: "memory");
#pragma unroll
            for (int i = 0; i < 6; i++) {
                const uint32_t w[4] = {xo[i].x, xo[i].y, xo[i].z, xo[i].w};
#pragma unroll
                for (int e = 0; e < 4; e++) {
                    const int k = 4 * i + e;
                    if (k < 22) dst[(k >> 1) * 256 + (k & 1) * 32] = pack2(fmaf(az1[2 * k], lo_f(w[e]), acc[2 * k]), fmaf(az1[2 * k + 1], hi_f(w[e]), acc[2 * k + 1]));
                }
            }
            bar_sync(2 + wg, 128);
            if (elect) { st_release(&S->fu[(2 * r + wg) * 32 + j], epoch); mbar_arrive_cluster(BAR(B_LU + rank), wg); }
            STAMP(18);
        }
        {
            float acc[32];
            const uint64_t da = mkdesc(sb + OFF_U, 1024, 128, 0), db0 = mkdesc(sb + wg * 8192, 8192, 1024, 1);
#pragma unroll 1
            for (int q = 0; q < 4; q++) {
#pragma unroll
                for (int i = 0; i < 3; i++) {
                    const int b = 3 * q + i;
                    mbar_wait(BAR(B_WT + b), 0);
                    if (i < 2) mbar_wait(BAR(B_U + 2 * q + i), 0);
                    if (b == 0) STAMP(19);
                    const uint64_t db = db0 + (P3_WT(b) >> 4), dk = da + (q * 11 + i * 4) * 128;
                    wg_fence();
#pragma unroll
                    for (int ks = 0; ks < (i < 2 ? 4 : 3); ks++) wgmma_n64_t01(acc, dk + ks * 128, db + ks * 128, (b | ks) != 0);
                    wg_commit();
                    wg_wait<1>();
                    if (elect && b >= 1 && b <= 5) mbar_arrive(BAR(B_ET + b - 1));
                }
            }
            wg_wait<0>();
            pin(acc);
            STAMP(20);
            const uint32_t stg = sb + P3_WT(5) + wg * 8192;
            const uint32_t srow = stg + (16 * w4 + (lane & 15)) * 128;
#pragma unroll
            for (int i = 0; i < 8; i++) {
                hres[2 * i] = pack2(lo_f(hres[2 * i]) + acc[4 * i], hi_f(hres[2 * i]) + acc[4 * i + 1]);
                hres[2 * i + 1] = pack2(lo_f(hres[2 * i + 1]) + acc[4 * i + 2], hi_f(hres[2 * i + 1]) + acc[4 * i + 3]);
            }
#pragma unroll
            for (int i = 0; i < 4; i++) stsm4(srow + (((2 * i + (lane >> 4)) ^ (lane & 7)) * 16), hres[4 * i], hres[4 * i + 1], hres[4 * i + 2], hres[4 * i + 3]);
            fence_async_smem();
            bar_sync(2 + wg, 128);
            if (elect) {
                asm volatile("cp.async.bulk.tensor.2d.global.shared::cta.bulk_group [%0, {%2, %3}], [%1];"
                             :: "l"(&P.mout), "r"(stg), "r"(128 * c4 + 64 * wg), "r"(64 * rh) : "memory");
                asm volatile("cp.async.bulk.commit_group;" ::: "memory");
                asm volatile("cp.async.bulk.wait_group.read 0;" ::: "memory");
                mbar_arrive(BAR(B_END));
            }
            STAMP(21);
        }
    }
}

typedef CUresult (*EncodeFn)(CUtensorMap*, CUtensorMapDataType, cuuint32_t, void*, const cuuint64_t*, const cuuint64_t*, const cuuint32_t*,
                             const cuuint32_t*, CUtensorMapInterleave, CUtensorMapSwizzle, CUtensorMapL2promotion, CUtensorMapFloatOOBfill);

static void make_map(EncodeFn enc, CUtensorMap* m, const void* ptr, int rows, int cols, int box_rows, int box_cols, CUtensorMapSwizzle sw) {
    cuuint64_t gd[2] = {(cuuint64_t)cols, (cuuint64_t)rows};
    cuuint64_t gs[1] = {(cuuint64_t)cols * 2};
    cuuint32_t bx[2] = {(cuuint32_t)box_cols, (cuuint32_t)box_rows}, es[2] = {1, 1};
    enc(m, CU_TENSOR_MAP_DATA_TYPE_BFLOAT16, 2, (void*)ptr, gd, gs, bx, es, CU_TENSOR_MAP_INTERLEAVE_NONE, sw,
        CU_TENSOR_MAP_L2_PROMOTION_L2_256B, CU_TENSOR_MAP_FLOAT_OOB_FILL_NONE);
}

extern "C" void kernel_launch(void* const* d_in, const int* in_sizes, int n_in, void* d_out, int out_size) {
    static EncodeFn enc = nullptr;
    static int use_smid = 0;
    static Scratch* scr = nullptr;
    cudaLaunchConfig_t cfg = {};
    cudaLaunchAttribute at[1];
    at[0].id = cudaLaunchAttributeClusterDimension;
    at[0].val.clusterDim.x = 2; at[0].val.clusterDim.y = 1; at[0].val.clusterDim.z = 1;
    cfg.blockDim = dim3(384); cfg.dynamicSmemBytes = SMEM_BYTES; cfg.stream = cudaStreamPerThread;
    cfg.attrs = at; cfg.numAttrs = 1;
    if (!enc) {
        void* fn = nullptr; cudaDriverEntryPointQueryResult qr;
        cudaGetDriverEntryPoint("cuTensorMapEncodeTiled", &fn, cudaEnableDefault, &qr);
        enc = (EncodeFn)fn;
        cudaFuncSetAttribute(fused_kernel<true>, cudaFuncAttributeMaxDynamicSharedMemorySize, SMEM_BYTES);
        cudaFuncSetAttribute(fused_kernel<false>, cudaFuncAttributeMaxDynamicSharedMemorySize, SMEM_BYTES);
        int nsm = 0, ncl = 0;
        cudaDeviceGetAttribute(&nsm, cudaDevAttrMultiProcessorCount, 0);
        cfg.gridDim = dim3(132);
        cudaOccupancyMaxActiveClusters(&ncl, fused_kernel<true>, &cfg);
        use_smid = (nsm == 132 && ncl == 66);
        cudaGetSymbolAddress((void**)&scr, g_scr);
    }
    Params P;
    const bf16 *x = (const bf16*)d_in[0], *wqkv = (const bf16*)d_in[1], *wphi = (const bf16*)d_in[2], *wo = (const bf16*)d_in[3];
    const bf16 *win = (const bf16*)d_in[5], *wsp = (const bf16*)d_in[6], *bsp = (const bf16*)d_in[7], *wout = (const bf16*)d_in[8];
    make_map(enc, &P.mx, x, 2048, 512, 128, 64, CU_TENSOR_MAP_SWIZZLE_128B);
    make_map(enc, &P.mwqkv, wqkv, 512, 1536, 64, 64, CU_TENSOR_MAP_SWIZZLE_128B);
    make_map(enc, &P.mw32, wqkv, 512, 1536, 32, 64, CU_TENSOR_MAP_SWIZZLE_128B);
    make_map(enc, &P.mwo, wo, 512, 512, 256, 64, CU_TENSOR_MAP_SWIZZLE_128B);
    make_map(enc, &P.mwsp, wsp, 2048, 2048, 128, 64, CU_TENSOR_MAP_SWIZZLE_128B);
    make_map(enc, &P.mwout, wout, 688, 512, 64, 64, CU_TENSOR_MAP_SWIZZLE_128B);
    make_map(enc, &P.mout, d_out, 2048, 512, 64, 64, CU_TENSOR_MAP_SWIZZLE_128B);
    cfg.gridDim = dim3(use_smid ? 132 : 128);
    cudaLaunchKernelEx(&cfg, use_smid ? fused_kernel<true> : fused_kernel<false>, x, scr, wphi, bsp, win, wout, P);
}
```
